```python
import torch

def _softmax(x, axis=-1):
    return torch.softmax(x, dim=axis)

def _gelu(x):
    return torch.nn.functional.gelu(x, approximate='tanh')

def _silu(x):
    return torch.nn.functional.silu(x)

def _sigmoid(x):
    return torch.sigmoid(x)

def _layernorm(x, axis=-1, eps=1e-05):
    m = x.mean(dim=axis, keepdim=True)
    v = x.var(dim=axis, keepdim=True, unbiased=False)
    return (x - m) / torch.sqrt(v + eps)

def _scatter_add(tgt, idx, src, axis=0):
    return tgt.clone().index_add_(axis, idx, src)

def _segment_sum(src, seg, n):
    out = torch.zeros((n,) + src.shape[1:], dtype=src.dtype)
    return out.index_add_(0, seg, src)

def _pad(x, pw):
    flat = tuple((v for pair in reversed(pw) for v in pair))
    return torch.nn.functional.pad(x, flat)
kernel_name = 'adaLN_cond__sliding_block_cached__mixer_s_mlp__prompt'

def setup_inputs():

    _w = lambda a: (lambda t: t.to(torch.bfloat16) if t.is_floating_point() else t)(torch.as_tensor(a))

    def _A_setup():
        B, Sq, D = (1, 2048, 448)
        Hq, Hkv, Sk, Dh = (16, 8, 2048, 256)
        assert Hq % Hkv == 0, (Hq, Hkv)
        return {'x': _w((lambda *s: torch.randn(*s, dtype=torch.bfloat16) * 0.1)(B, Sq, D)), 'k_cache': _w((lambda *s: torch.randn(*s, dtype=torch.bfloat16) * 0.8)(B, Hkv, Sk, Dh)), 'v_cache': _w((lambda *s: torch.randn(*s, dtype=torch.bfloat16) * 0.8)(B, Hkv, Sk, Dh)), 'wq': _w((lambda *s: torch.randn(*s, dtype=torch.bfloat16) * 0.8)(D, Hq * Dh) * D ** (-0.5)), 'wo': _w((lambda *s: torch.randn(*s, dtype=torch.bfloat16) * 0.8)(Hq * Dh, D) * (Hq * Dh) ** (-0.5))}
    _A_in = _A_setup()

    def _B_setup():
        B, S, D, F = (1, 2048, 448, 1792)
        return {'x': _w((lambda *s: torch.randn(*s, dtype=torch.bfloat16) * 0.1)(B, S, D)), 'w1': _w((lambda *s: torch.randn(*s, dtype=torch.bfloat16) * 3.2)(D, D) * D ** (-0.5)), 'w2': _w((lambda *s: torch.randn(*s, dtype=torch.bfloat16) * 3.2)(D, D) * D ** (-0.5)), 'w3': _w((lambda *s: torch.randn(*s, dtype=torch.bfloat16) * 3.2)(D, F) * D ** (-0.5)), 'w4': _w((lambda *s: torch.randn(*s, dtype=torch.bfloat16) * 3.2)(F, D) * F ** (-0.5))}
    _B_in = _B_setup()
    return {'A_x': _A_in['x'], 'A_k_cache': _A_in['k_cache'], 'A_v_cache': _A_in['v_cache'], 'A_wq': _A_in['wq'], 'A_wo': _A_in['wo'], 'B_x': _B_in['x'], 'B_w1': _B_in['w1'], 'B_w2': _B_in['w2'], 'B_w3': _B_in['w3'], 'B_w4': _B_in['w4'], 'c': _w((lambda *s: torch.randn(*s, dtype=torch.bfloat16) * 0.2)(1, 448) * 8.0), 'w_mod': _w((lambda *s: torch.randn(*s, dtype=torch.bfloat16) * 0.2)(448, 6 * 448) * 448 ** (-0.5) * 8.0)}

def reference(A_x, A_k_cache, A_v_cache, A_wq, A_wo, B_x, B_w1, B_w2, B_w3, B_w4, c, w_mod):

    def _A_ref(x, k_cache, v_cache, wq, wo):
        B, Sq, D = x.shape
        Hq, Dh = (16, 256)
        Hkv, Sk = (k_cache.shape[1], k_cache.shape[2])
        W = min(4096, max(256, Sk // 4))
        rep = Hq // Hkv
        q = (lambda x, *d: x.permute(*d))((x @ wq).reshape(B, Sq, Hq, Dh), 0, 2, 1, 3)
        k = (lambda x, n, axis: torch.repeat_interleave(x, n, dim=axis))(k_cache[:, :, Sk - W:, :], rep, axis=1)
        v = (lambda x, n, axis: torch.repeat_interleave(x, n, dim=axis))(v_cache[:, :, Sk - W:, :], rep, axis=1)
        scores = torch.einsum('bhqd,bhkd->bhqk', q, k) * Dh ** (-0.5)
        p = _softmax(scores, axis=-1)
        o = torch.einsum('bhqk,bhkd->bhqd', p, v)
        return (lambda x, *d: x.permute(*d))(o, 0, 2, 1, 3).reshape(B, Sq, Hq * Dh) @ wo

    def _B_ref(x, w1, w2, w3, w4):
        B, S, D = x.shape
        h = _gelu(_layernorm(x, axis=-1) @ w1)
        c = D // 4
        g0 = _pad(h[:, :, 0 * c:1 * c], ((0, 0), (1, 0), (0, 0)))[:, :S, :]
        g1 = _pad(h[:, :, 1 * c:2 * c], ((0, 0), (0, 1), (0, 0)))[:, 1:, :]
        g2 = _pad(h[:, :, 2 * c:3 * c], ((0, 0), (2, 0), (0, 0)))[:, :S, :]
        g3 = _pad(h[:, :, 3 * c:], ((0, 0), (0, 2), (0, 0)))[:, 2:, :]
        hs = torch.concatenate([g0, g1, g2, g3], axis=-1) @ w2
        x1 = x + hs
        h2 = _gelu(_layernorm(x1, axis=-1) @ w3) @ w4
        return x1 + h2
    x = A_x
    mod = (_silu(c) @ w_mod).reshape(c.shape[0], 6, 1, -1)
    sa, ca, ga, sb, cb, gb = (mod[:, 0].clone(), mod[:, 1].clone(), mod[:, 2].clone(), mod[:, 3].clone(), mod[:, 4].clone(), mod[:, 5].clone())
    h = _layernorm(x, axis=-1) * (1 + ca) + sa
    x = x + ga * _A_ref(h, A_k_cache, A_v_cache, A_wq, A_wo)
    h = _layernorm(x, axis=-1) * (1 + cb) + sb
    x = x + gb * _B_ref(h, B_w1, B_w2, B_w3, B_w4)
    return x
```

```cpp
#include <cuda_runtime.h>
#include <cuda_bf16.h>
#include <cuda.h>
#include <stdint.h>
#include <string.h>

typedef __nv_bfloat16 bf16;

constexpr int S_ = 2048;
constexpr int D_ = 448;
constexpr int DH = 256;
constexpr int HQ = 16;
constexpr int HKV = 8;
constexpr int SK = 2048;
constexpr int WIN = 512;
constexpr int F_ = 1792;
constexpr float LN_EPS = 1e-5f;

__device__ __align__(16) float g_mod[6 * D_];
__device__ __align__(16) float g_colsum3[F_];
__device__ __align__(16) float g_colsum1[D_];
__device__ __align__(1024) bf16 g_H[S_ * D_];
__device__ __align__(1024) bf16 g_park[128 * 128 * DH];
__device__ __align__(1024) bf16 g_A[S_ * D_];
__device__ __align__(1024) bf16 g_hb[S_ * D_];
__device__ __align__(16) float2 g_hstat[S_];
__device__ __align__(1024) bf16 g_G[(S_ + 4) * D_];
__device__ __align__(1024) bf16 g_y[S_ * D_];
__device__ __align__(16) float2 g_ystat[8 * S_];

__device__ __forceinline__ uint32_t smem_u32(const void* p) { return (uint32_t)__cvta_generic_to_shared(p); }
__device__ __forceinline__ void mbar_init(uint32_t bar, uint32_t cnt) {
    asm volatile("mbarrier.init.shared::cta.b64 [%0], %1;" ::"r"(bar), "r"(cnt) : "memory");
}
__device__ __forceinline__ void mbar_expect_tx(uint32_t bar, uint32_t bytes) {
    asm volatile("mbarrier.arrive.expect_tx.shared::cta.b64 _, [%0], %1;" ::"r"(bar), "r"(bytes) : "memory");
}
__device__ __forceinline__ void mbar_arrive(uint32_t bar) {
    asm volatile("mbarrier.arrive.shared::cta.b64 _, [%0];" ::"r"(bar) : "memory");
}
__device__ __forceinline__ void mbar_wait(uint32_t bar, uint32_t parity) {
    asm volatile(
        "{\n.reg .pred p;\n"
        "WAIT_LOOP:\n"
        "mbarrier.try_wait.parity.shared::cta.b64 p, [%0], %1;\n"
        "@p bra WAIT_DONE;\n"
        "bra WAIT_LOOP;\n"
        "WAIT_DONE:\n}\n" ::"r"(bar), "r"(parity) : "memory");
}
__device__ __forceinline__ bool elect_one() {
    uint32_t pred;
    asm volatile("{\n.reg .pred p;\nelect.sync _|p, 0xffffffff;\nselp.u32 %0, 1, 0, p;\n}\n" : "=r"(pred));
    return pred != 0;
}
__device__ __forceinline__ void fence_barrier_init() { asm volatile("fence.mbarrier_init.release.cluster;" ::: "memory"); }
__device__ __forceinline__ void fence_proxy_async() { asm volatile("fence.proxy.async.shared::cta;" ::: "memory"); }
__device__ __forceinline__ void named_sync(int id, int n) { asm volatile("bar.sync %0, %1;" ::"r"(id), "r"(n) : "memory"); }
template <int ID, int N> __device__ __forceinline__ void named_sync_imm() { asm volatile("bar.sync %0, %1;" ::"n"(ID), "n"(N) : "memory"); }
__device__ __forceinline__ void named_arrive(int id, int n) { asm volatile("bar.arrive %0, %1;" ::"r"(id), "r"(n) : "memory"); }
__device__ __forceinline__ void pdl_wait() { asm volatile("griddepcontrol.wait;" ::: "memory"); }
__device__ __forceinline__ void pdl_launch() { asm volatile("griddepcontrol.launch_dependents;" ::: "memory"); }
__device__ __forceinline__ void tma_prefetch_desc(const CUtensorMap* m) {
    asm volatile("prefetch.tensormap [%0];" ::"l"(m) : "memory");
}
__device__ __forceinline__ void tma_load_2d(uint32_t dst, const CUtensorMap* m, uint32_t bar, int c0, int c1) {
    asm volatile("cp.async.bulk.tensor.2d.shared::cluster.global.mbarrier::complete_tx::bytes [%0], [%1, {%3, %4}], [%2];"
                 ::"r"(dst), "l"(m), "r"(bar), "r"(c0), "r"(c1) : "memory");
}
__device__ __forceinline__ void tma_load_2d_mc(uint32_t dst, const CUtensorMap* m, uint32_t bar, int c0, int c1) {
    asm volatile("cp.async.bulk.tensor.2d.shared::cluster.global.mbarrier::complete_tx::bytes.multicast::cluster [%0], [%1, {%3, %4}], [%2], %5;"
                 ::"r"(dst), "l"(m), "r"(bar), "r"(c0), "r"(c1), "h"((uint16_t)3) : "memory");
}
__device__ __forceinline__ void tma_load_3d_mc(uint32_t dst, const CUtensorMap* m, uint32_t bar, int c0, int c1, int c2) {
    asm volatile("cp.async.bulk.tensor.3d.shared::cluster.global.mbarrier::complete_tx::bytes.multicast::cluster [%0], [%1, {%3, %4, %5}], [%2], %6;"
                 ::"r"(dst), "l"(m), "r"(bar), "r"(c0), "r"(c1), "r"(c2), "h"((uint16_t)3) : "memory");
}
__device__ __forceinline__ uint32_t map_cluster(uint32_t addr, uint32_t rank) {
    uint32_t r;
    asm("mapa.shared::cluster.u32 %0, %1, %2;" : "=r"(r) : "r"(addr), "r"(rank));
    return r;
}
__device__ __forceinline__ void mbar_arrive_cluster(uint32_t addr) {
    asm volatile("mbarrier.arrive.shared::cluster.b64 _, [%0];" ::"r"(addr) : "memory");
}
__device__ __forceinline__ void cluster_sync() {
    asm volatile("barrier.cluster.arrive.relaxed.aligned;\nbarrier.cluster.wait.aligned;" ::: "memory");
}
__device__ __forceinline__ void tma_store_2d(const CUtensorMap* m, uint32_t src, int c0, int c1) {
    asm volatile("cp.async.bulk.tensor.2d.global.shared::cta.bulk_group [%0, {%2, %3}], [%1];"
                 ::"l"(m), "r"(src), "r"(c0), "r"(c1) : "memory");
}
__device__ __forceinline__ void tma_reduce_add_2d(const CUtensorMap* m, uint32_t src, int c0, int c1) {
    asm volatile("cp.reduce.async.bulk.tensor.2d.global.shared::cta.add.tile.bulk_group [%0, {%2, %3}], [%1];"
                 ::"l"(m), "r"(src), "r"(c0), "r"(c1) : "memory");
}
__device__ __forceinline__ void l2_prefetch(const void* p, uint32_t bytes) {
    asm volatile("cp.async.bulk.prefetch.L2.global [%0], %1;" ::"l"(p), "r"(bytes) : "memory");
}
__device__ __forceinline__ void bulk_commit() { asm volatile("cp.async.bulk.commit_group;" ::: "memory"); }
__device__ __forceinline__ void bulk_wait_read0() { asm volatile("cp.async.bulk.wait_group.read 0;" ::: "memory"); }
__device__ __forceinline__ void bulk_wait0() { asm volatile("cp.async.bulk.wait_group 0;" ::: "memory"); }

__device__ __forceinline__ void wg_fence() { asm volatile("wgmma.fence.sync.aligned;" ::: "memory"); }
__device__ __forceinline__ void wg_commit() { asm volatile("wgmma.commit_group.sync.aligned;" ::: "memory"); }
template <int N> __device__ __forceinline__ void wg_wait() { asm volatile("wgmma.wait_group.sync.aligned %0;" ::"n"(N) : "memory"); }
template <int N> __device__ __forceinline__ void fence_regs(float (&d)[N]) {
#pragma unroll
    for (int i = 0; i < N; i++) asm volatile("" : "+f"(d[i])::"memory");
}
template <int N> __device__ __forceinline__ void fence_regs(uint32_t (&d)[N]) {
#pragma unroll
    for (int i = 0; i < N; i++) asm volatile("" : "+r"(d[i])::"memory");
}
template <int R> __device__ __forceinline__ void reg_inc() { asm volatile("setmaxnreg.inc.sync.aligned.u32 %0;" ::"n"(R)); }
template <int R> __device__ __forceinline__ void reg_dec() { asm volatile("setmaxnreg.dec.sync.aligned.u32 %0;" ::"n"(R)); }

__device__ __forceinline__ uint64_t make_desc(uint32_t addr, uint32_t lbo, uint32_t sbo) {
    return (uint64_t)((addr & 0x3FFFF) >> 4) | ((uint64_t)(lbo >> 4) << 16) | ((uint64_t)(sbo >> 4) << 32) | (1ull << 62);
}
__device__ __forceinline__ uint32_t pack_bf16(float lo, float hi) {
    uint32_t r;
    asm("cvt.rn.bf16x2.f32 %0, %1, %2;" : "=r"(r) : "f"(hi), "f"(lo));
    return r;
}
__device__ __forceinline__ float bf16_lo(uint32_t v) { return __uint_as_float(v << 16); }
__device__ __forceinline__ float bf16_hi(uint32_t v) { return __uint_as_float(v & 0xffff0000u); }
__device__ __forceinline__ float round_bf16(float x) { return __bfloat162float(__float2bfloat16_rn(x)); }
__device__ __forceinline__ void round2_bf16(float& a, float& b) {
    const uint32_t p = pack_bf16(a, b);
    a = bf16_lo(p); b = bf16_hi(p);
}
__device__ __forceinline__ float ex2f(float x) {
    float r;
    asm("ex2.approx.ftz.f32 %0, %1;" : "=f"(r) : "f"(x));
    return r;
}
__device__ __forceinline__ void stmatrix_x4(uint32_t addr, uint32_t r0, uint32_t r1, uint32_t r2, uint32_t r3) {
    asm volatile("stmatrix.sync.aligned.m8n8.x4.shared.b16 [%0], {%1, %2, %3, %4};" ::"r"(addr), "r"(r0), "r"(r1), "r"(r2), "r"(r3) : "memory");
}
__device__ __forceinline__ float gelu_tanh(float x) {
    const float k0 = 0.7978845608028654f, k1 = 0.7978845608028654f * 0.044715f;
    float u = x * fmaf(k1, x * x, k0);
    float t;
    asm("tanh.approx.f32 %0, %1;" : "=f"(t) : "f"(u));
    float hx = 0.5f * x;
    return fmaf(hx, t, hx);
}

template <int SZ> __device__ __forceinline__ void wgmma_n256_ss(float (&d)[SZ], uint64_t da, uint64_t db, int sd) {
    asm volatile("{\n.reg .pred p;\nsetp.ne.b32 p, %130, 0;\n"
        "wgmma.mma_async.sync.aligned.m64n256k16.f32.bf16.bf16 {%0, %1, %2, %3, %4, %5, %6, %7, %8, %9, %10, %11, %12, %13, %14, %15, %16, %17, %18, %19, %20, %21, %22, %23, %24, %25, %26, %27, %28, %29, %30, %31, %32, %33, %34, %35, %36, %37, %38, %39, %40, %41, %42, %43, %44, %45, %46, %47, %48, %49, %50, %51, %52, %53, %54, %55, %56, %57, %58, %59, %60, %61, %62, %63, %64, %65, %66, %67, %68, %69, %70, %71, %72, %73, %74, %75, %76, %77, %78, %79, %80, %81, %82, %83, %84, %85, %86, %87, %88, %89, %90, %91, %92, %93, %94, %95, %96, %97, %98, %99, %100, %101, %102, %103, %104, %105, %106, %107, %108, %109, %110, %111, %112, %113, %114, %115, %116, %117, %118, %119, %120, %121, %122, %123, %124, %125, %126, %127}, %128, %129, p, 1, 1, 0, 1;\n}\n"
        : "+f"(d[0]), "+f"(d[1]), "+f"(d[2]), "+f"(d[3]), "+f"(d[4]), "+f"(d[5]), "+f"(d[6]), "+f"(d[7]), "+f"(d[8]), "+f"(d[9]), "+f"(d[10]), "+f"(d[11]), "+f"(d[12]), "+f"(d[13]), "+f"(d[14]), "+f"(d[15]), "+f"(d[16]), "+f"(d[17]), "+f"(d[18]), "+f"(d[19]), "+f"(d[20]), "+f"(d[21]), "+f"(d[22]), "+f"(d[23]), "+f"(d[24]), "+f"(d[25]), "+f"(d[26]), "+f"(d[27]), "+f"(d[28]), "+f"(d[29]), "+f"(d[30]), "+f"(d[31]), "+f"(d[32]), "+f"(d[33]), "+f"(d[34]), "+f"(d[35]), "+f"(d[36]), "+f"(d[37]), "+f"(d[38]), "+f"(d[39]), "+f"(d[40]), "+f"(d[41]), "+f"(d[42]), "+f"(d[43]), "+f"(d[44]), "+f"(d[45]), "+f"(d[46]), "+f"(d[47]), "+f"(d[48]), "+f"(d[49]), "+f"(d[50]), "+f"(d[51]), "+f"(d[52]), "+f"(d[53]), "+f"(d[54]), "+f"(d[55]), "+f"(d[56]), "+f"(d[57]), "+f"(d[58]), "+f"(d[59]), "+f"(d[60]), "+f"(d[61]), "+f"(d[62]), "+f"(d[63]), "+f"(d[64]), "+f"(d[65]), "+f"(d[66]), "+f"(d[67]), "+f"(d[68]), "+f"(d[69]), "+f"(d[70]), "+f"(d[71]), "+f"(d[72]), "+f"(d[73]), "+f"(d[74]), "+f"(d[75]), "+f"(d[76]), "+f"(d[77]), "+f"(d[78]), "+f"(d[79]), "+f"(d[80]), "+f"(d[81]), "+f"(d[82]), "+f"(d[83]), "+f"(d[84]), "+f"(d[85]), "+f"(d[86]), "+f"(d[87]), "+f"(d[88]), "+f"(d[89]), "+f"(d[90]), "+f"(d[91]), "+f"(d[92]), "+f"(d[93]), "+f"(d[94]), "+f"(d[95]), "+f"(d[96]), "+f"(d[97]), "+f"(d[98]), "+f"(d[99]), "+f"(d[100]), "+f"(d[101]), "+f"(d[102]), "+f"(d[103]), "+f"(d[104]), "+f"(d[105]), "+f"(d[106]), "+f"(d[107]), "+f"(d[108]), "+f"(d[109]), "+f"(d[110]), "+f"(d[111]), "+f"(d[112]), "+f"(d[113]), "+f"(d[114]), "+f"(d[115]), "+f"(d[116]), "+f"(d[117]), "+f"(d[118]), "+f"(d[119]), "+f"(d[120]), "+f"(d[121]), "+f"(d[122]), "+f"(d[123]), "+f"(d[124]), "+f"(d[125]), "+f"(d[126]), "+f"(d[127])
        : "l"(da), "l"(db), "r"(sd));
}
template <int SZ> __device__ __forceinline__ void wgmma_n256_rs(float (&d)[SZ], uint32_t a0, uint32_t a1, uint32_t a2, uint32_t a3, uint64_t db, int sd) {
    asm volatile("{\n.reg .pred p;\nsetp.ne.b32 p, %133, 0;\n"
        "wgmma.mma_async.sync.aligned.m64n256k16.f32.bf16.bf16 {%0, %1, %2, %3, %4, %5, %6, %7, %8, %9, %10, %11, %12, %13, %14, %15, %16, %17, %18, %19, %20, %21, %22, %23, %24, %25, %26, %27, %28, %29, %30, %31, %32, %33, %34, %35, %36, %37, %38, %39, %40, %41, %42, %43, %44, %45, %46, %47, %48, %49, %50, %51, %52, %53, %54, %55, %56, %57, %58, %59, %60, %61, %62, %63, %64, %65, %66, %67, %68, %69, %70, %71, %72, %73, %74, %75, %76, %77, %78, %79, %80, %81, %82, %83, %84, %85, %86, %87, %88, %89, %90, %91, %92, %93, %94, %95, %96, %97, %98, %99, %100, %101, %102, %103, %104, %105, %106, %107, %108, %109, %110, %111, %112, %113, %114, %115, %116, %117, %118, %119, %120, %121, %122, %123, %124, %125, %126, %127}, {%128, %129, %130, %131}, %132, p, 1, 1, 1;\n}\n"
        : "+f"(d[0]), "+f"(d[1]), "+f"(d[2]), "+f"(d[3]), "+f"(d[4]), "+f"(d[5]), "+f"(d[6]), "+f"(d[7]), "+f"(d[8]), "+f"(d[9]), "+f"(d[10]), "+f"(d[11]), "+f"(d[12]), "+f"(d[13]), "+f"(d[14]), "+f"(d[15]), "+f"(d[16]), "+f"(d[17]), "+f"(d[18]), "+f"(d[19]), "+f"(d[20]), "+f"(d[21]), "+f"(d[22]), "+f"(d[23]), "+f"(d[24]), "+f"(d[25]), "+f"(d[26]), "+f"(d[27]), "+f"(d[28]), "+f"(d[29]), "+f"(d[30]), "+f"(d[31]), "+f"(d[32]), "+f"(d[33]), "+f"(d[34]), "+f"(d[35]), "+f"(d[36]), "+f"(d[37]), "+f"(d[38]), "+f"(d[39]), "+f"(d[40]), "+f"(d[41]), "+f"(d[42]), "+f"(d[43]), "+f"(d[44]), "+f"(d[45]), "+f"(d[46]), "+f"(d[47]), "+f"(d[48]), "+f"(d[49]), "+f"(d[50]), "+f"(d[51]), "+f"(d[52]), "+f"(d[53]), "+f"(d[54]), "+f"(d[55]), "+f"(d[56]), "+f"(d[57]), "+f"(d[58]), "+f"(d[59]), "+f"(d[60]), "+f"(d[61]), "+f"(d[62]), "+f"(d[63]), "+f"(d[64]), "+f"(d[65]), "+f"(d[66]), "+f"(d[67]), "+f"(d[68]), "+f"(d[69]), "+f"(d[70]), "+f"(d[71]), "+f"(d[72]), "+f"(d[73]), "+f"(d[74]), "+f"(d[75]), "+f"(d[76]), "+f"(d[77]), "+f"(d[78]), "+f"(d[79]), "+f"(d[80]), "+f"(d[81]), "+f"(d[82]), "+f"(d[83]), "+f"(d[84]), "+f"(d[85]), "+f"(d[86]), "+f"(d[87]), "+f"(d[88]), "+f"(d[89]), "+f"(d[90]), "+f"(d[91]), "+f"(d[92]), "+f"(d[93]), "+f"(d[94]), "+f"(d[95]), "+f"(d[96]), "+f"(d[97]), "+f"(d[98]), "+f"(d[99]), "+f"(d[100]), "+f"(d[101]), "+f"(d[102]), "+f"(d[103]), "+f"(d[104]), "+f"(d[105]), "+f"(d[106]), "+f"(d[107]), "+f"(d[108]), "+f"(d[109]), "+f"(d[110]), "+f"(d[111]), "+f"(d[112]), "+f"(d[113]), "+f"(d[114]), "+f"(d[115]), "+f"(d[116]), "+f"(d[117]), "+f"(d[118]), "+f"(d[119]), "+f"(d[120]), "+f"(d[121]), "+f"(d[122]), "+f"(d[123]), "+f"(d[124]), "+f"(d[125]), "+f"(d[126]), "+f"(d[127])
        : "r"(a0), "r"(a1), "r"(a2), "r"(a3), "l"(db), "r"(sd));
}
template <int SZ> __device__ __forceinline__ void wgmma_n192_ss(float (&d)[SZ], uint64_t da, uint64_t db, int sd) {
    asm volatile("{\n.reg .pred p;\nsetp.ne.b32 p, %98, 0;\n"
        "wgmma.mma_async.sync.aligned.m64n192k16.f32.bf16.bf16 {%0, %1, %2, %3, %4, %5, %6, %7, %8, %9, %10, %11, %12, %13, %14, %15, %16, %17, %18, %19, %20, %21, %22, %23, %24, %25, %26, %27, %28, %29, %30, %31, %32, %33, %34, %35, %36, %37, %38, %39, %40, %41, %42, %43, %44, %45, %46, %47, %48, %49, %50, %51, %52, %53, %54, %55, %56, %57, %58, %59, %60, %61, %62, %63, %64, %65, %66, %67, %68, %69, %70, %71, %72, %73, %74, %75, %76, %77, %78, %79, %80, %81, %82, %83, %84, %85, %86, %87, %88, %89, %90, %91, %92, %93, %94, %95}, %96, %97, p, 1, 1, 0, 1;\n}\n"
        : "+f"(d[0]), "+f"(d[1]), "+f"(d[2]), "+f"(d[3]), "+f"(d[4]), "+f"(d[5]), "+f"(d[6]), "+f"(d[7]), "+f"(d[8]), "+f"(d[9]), "+f"(d[10]), "+f"(d[11]), "+f"(d[12]), "+f"(d[13]), "+f"(d[14]), "+f"(d[15]), "+f"(d[16]), "+f"(d[17]), "+f"(d[18]), "+f"(d[19]), "+f"(d[20]), "+f"(d[21]), "+f"(d[22]), "+f"(d[23]), "+f"(d[24]), "+f"(d[25]), "+f"(d[26]), "+f"(d[27]), "+f"(d[28]), "+f"(d[29]), "+f"(d[30]), "+f"(d[31]), "+f"(d[32]), "+f"(d[33]), "+f"(d[34]), "+f"(d[35]), "+f"(d[36]), "+f"(d[37]), "+f"(d[38]), "+f"(d[39]), "+f"(d[40]), "+f"(d[41]), "+f"(d[42]), "+f"(d[43]), "+f"(d[44]), "+f"(d[45]), "+f"(d[46]), "+f"(d[47]), "+f"(d[48]), "+f"(d[49]), "+f"(d[50]), "+f"(d[51]), "+f"(d[52]), "+f"(d[53]), "+f"(d[54]), "+f"(d[55]), "+f"(d[56]), "+f"(d[57]), "+f"(d[58]), "+f"(d[59]), "+f"(d[60]), "+f"(d[61]), "+f"(d[62]), "+f"(d[63]), "+f"(d[64]), "+f"(d[65]), "+f"(d[66]), "+f"(d[67]), "+f"(d[68]), "+f"(d[69]), "+f"(d[70]), "+f"(d[71]), "+f"(d[72]), "+f"(d[73]), "+f"(d[74]), "+f"(d[75]), "+f"(d[76]), "+f"(d[77]), "+f"(d[78]), "+f"(d[79]), "+f"(d[80]), "+f"(d[81]), "+f"(d[82]), "+f"(d[83]), "+f"(d[84]), "+f"(d[85]), "+f"(d[86]), "+f"(d[87]), "+f"(d[88]), "+f"(d[89]), "+f"(d[90]), "+f"(d[91]), "+f"(d[92]), "+f"(d[93]), "+f"(d[94]), "+f"(d[95])
        : "l"(da), "l"(db), "r"(sd));
}
template <int SZ> __device__ __forceinline__ void wgmma_n192_rs(float (&d)[SZ], uint32_t a0, uint32_t a1, uint32_t a2, uint32_t a3, uint64_t db, int sd) {
    asm volatile("{\n.reg .pred p;\nsetp.ne.b32 p, %101, 0;\n"
        "wgmma.mma_async.sync.aligned.m64n192k16.f32.bf16.bf16 {%0, %1, %2, %3, %4, %5, %6, %7, %8, %9, %10, %11, %12, %13, %14, %15, %16, %17, %18, %19, %20, %21, %22, %23, %24, %25, %26, %27, %28, %29, %30, %31, %32, %33, %34, %35, %36, %37, %38, %39, %40, %41, %42, %43, %44, %45, %46, %47, %48, %49, %50, %51, %52, %53, %54, %55, %56, %57, %58, %59, %60, %61, %62, %63, %64, %65, %66, %67, %68, %69, %70, %71, %72, %73, %74, %75, %76, %77, %78, %79, %80, %81, %82, %83, %84, %85, %86, %87, %88, %89, %90, %91, %92, %93, %94, %95}, {%96, %97, %98, %99}, %100, p, 1, 1, 1;\n}\n"
        : "+f"(d[0]), "+f"(d[1]), "+f"(d[2]), "+f"(d[3]), "+f"(d[4]), "+f"(d[5]), "+f"(d[6]), "+f"(d[7]), "+f"(d[8]), "+f"(d[9]), "+f"(d[10]), "+f"(d[11]), "+f"(d[12]), "+f"(d[13]), "+f"(d[14]), "+f"(d[15]), "+f"(d[16]), "+f"(d[17]), "+f"(d[18]), "+f"(d[19]), "+f"(d[20]), "+f"(d[21]), "+f"(d[22]), "+f"(d[23]), "+f"(d[24]), "+f"(d[25]), "+f"(d[26]), "+f"(d[27]), "+f"(d[28]), "+f"(d[29]), "+f"(d[30]), "+f"(d[31]), "+f"(d[32]), "+f"(d[33]), "+f"(d[34]), "+f"(d[35]), "+f"(d[36]), "+f"(d[37]), "+f"(d[38]), "+f"(d[39]), "+f"(d[40]), "+f"(d[41]), "+f"(d[42]), "+f"(d[43]), "+f"(d[44]), "+f"(d[45]), "+f"(d[46]), "+f"(d[47]), "+f"(d[48]), "+f"(d[49]), "+f"(d[50]), "+f"(d[51]), "+f"(d[52]), "+f"(d[53]), "+f"(d[54]), "+f"(d[55]), "+f"(d[56]), "+f"(d[57]), "+f"(d[58]), "+f"(d[59]), "+f"(d[60]), "+f"(d[61]), "+f"(d[62]), "+f"(d[63]), "+f"(d[64]), "+f"(d[65]), "+f"(d[66]), "+f"(d[67]), "+f"(d[68]), "+f"(d[69]), "+f"(d[70]), "+f"(d[71]), "+f"(d[72]), "+f"(d[73]), "+f"(d[74]), "+f"(d[75]), "+f"(d[76]), "+f"(d[77]), "+f"(d[78]), "+f"(d[79]), "+f"(d[80]), "+f"(d[81]), "+f"(d[82]), "+f"(d[83]), "+f"(d[84]), "+f"(d[85]), "+f"(d[86]), "+f"(d[87]), "+f"(d[88]), "+f"(d[89]), "+f"(d[90]), "+f"(d[91]), "+f"(d[92]), "+f"(d[93]), "+f"(d[94]), "+f"(d[95])
        : "r"(a0), "r"(a1), "r"(a2), "r"(a3), "l"(db), "r"(sd));
}
template <int SZ> __device__ __forceinline__ void wgmma_n128_ss(float (&d)[SZ], uint64_t da, uint64_t db, int sd) {
    asm volatile("{\n.reg .pred p;\nsetp.ne.b32 p, %66, 0;\n"
        "wgmma.mma_async.sync.aligned.m64n128k16.f32.bf16.bf16 {%0, %1, %2, %3, %4, %5, %6, %7, %8, %9, %10, %11, %12, %13, %14, %15, %16, %17, %18, %19, %20, %21, %22, %23, %24, %25, %26, %27, %28, %29, %30, %31, %32, %33, %34, %35, %36, %37, %38, %39, %40, %41, %42, %43, %44, %45, %46, %47, %48, %49, %50, %51, %52, %53, %54, %55, %56, %57, %58, %59, %60, %61, %62, %63}, %64, %65, p, 1, 1, 0, 0;\n}\n"
        : "+f"(d[0]), "+f"(d[1]), "+f"(d[2]), "+f"(d[3]), "+f"(d[4]), "+f"(d[5]), "+f"(d[6]), "+f"(d[7]), "+f"(d[8]), "+f"(d[9]), "+f"(d[10]), "+f"(d[11]), "+f"(d[12]), "+f"(d[13]), "+f"(d[14]), "+f"(d[15]), "+f"(d[16]), "+f"(d[17]), "+f"(d[18]), "+f"(d[19]), "+f"(d[20]), "+f"(d[21]), "+f"(d[22]), "+f"(d[23]), "+f"(d[24]), "+f"(d[25]), "+f"(d[26]), "+f"(d[27]), "+f"(d[28]), "+f"(d[29]), "+f"(d[30]), "+f"(d[31]), "+f"(d[32]), "+f"(d[33]), "+f"(d[34]), "+f"(d[35]), "+f"(d[36]), "+f"(d[37]), "+f"(d[38]), "+f"(d[39]), "+f"(d[40]), "+f"(d[41]), "+f"(d[42]), "+f"(d[43]), "+f"(d[44]), "+f"(d[45]), "+f"(d[46]), "+f"(d[47]), "+f"(d[48]), "+f"(d[49]), "+f"(d[50]), "+f"(d[51]), "+f"(d[52]), "+f"(d[53]), "+f"(d[54]), "+f"(d[55]), "+f"(d[56]), "+f"(d[57]), "+f"(d[58]), "+f"(d[59]), "+f"(d[60]), "+f"(d[61]), "+f"(d[62]), "+f"(d[63])
        : "l"(da), "l"(db), "r"(sd));
}
template <int SZ> __device__ __forceinline__ void wgmma_n128_rs(float (&d)[SZ], uint32_t a0, uint32_t a1, uint32_t a2, uint32_t a3, uint64_t db, int sd) {
    asm volatile("{\n.reg .pred p;\nsetp.ne.b32 p, %69, 0;\n"
        "wgmma.mma_async.sync.aligned.m64n128k16.f32.bf16.bf16 {%0, %1, %2, %3, %4, %5, %6, %7, %8, %9, %10, %11, %12, %13, %14, %15, %16, %17, %18, %19, %20, %21, %22, %23, %24, %25, %26, %27, %28, %29, %30, %31, %32, %33, %34, %35, %36, %37, %38, %39, %40, %41, %42, %43, %44, %45, %46, %47, %48, %49, %50, %51, %52, %53, %54, %55, %56, %57, %58, %59, %60, %61, %62, %63}, {%64, %65, %66, %67}, %68, p, 1, 1, 1;\n}\n"
        : "+f"(d[0]), "+f"(d[1]), "+f"(d[2]), "+f"(d[3]), "+f"(d[4]), "+f"(d[5]), "+f"(d[6]), "+f"(d[7]), "+f"(d[8]), "+f"(d[9]), "+f"(d[10]), "+f"(d[11]), "+f"(d[12]), "+f"(d[13]), "+f"(d[14]), "+f"(d[15]), "+f"(d[16]), "+f"(d[17]), "+f"(d[18]), "+f"(d[19]), "+f"(d[20]), "+f"(d[21]), "+f"(d[22]), "+f"(d[23]), "+f"(d[24]), "+f"(d[25]), "+f"(d[26]), "+f"(d[27]), "+f"(d[28]), "+f"(d[29]), "+f"(d[30]), "+f"(d[31]), "+f"(d[32]), "+f"(d[33]), "+f"(d[34]), "+f"(d[35]), "+f"(d[36]), "+f"(d[37]), "+f"(d[38]), "+f"(d[39]), "+f"(d[40]), "+f"(d[41]), "+f"(d[42]), "+f"(d[43]), "+f"(d[44]), "+f"(d[45]), "+f"(d[46]), "+f"(d[47]), "+f"(d[48]), "+f"(d[49]), "+f"(d[50]), "+f"(d[51]), "+f"(d[52]), "+f"(d[53]), "+f"(d[54]), "+f"(d[55]), "+f"(d[56]), "+f"(d[57]), "+f"(d[58]), "+f"(d[59]), "+f"(d[60]), "+f"(d[61]), "+f"(d[62]), "+f"(d[63])
        : "r"(a0), "r"(a1), "r"(a2), "r"(a3), "l"(db), "r"(sd));
}
template <int SZ> __device__ __forceinline__ void wgmma_n224_ss(float (&d)[SZ], uint64_t da, uint64_t db, int sd) {
    asm volatile("{\n.reg .pred p;\nsetp.ne.b32 p, %114, 0;\n"
        "wgmma.mma_async.sync.aligned.m64n224k16.f32.bf16.bf16 {%0, %1, %2, %3, %4, %5, %6, %7, %8, %9, %10, %11, %12, %13, %14, %15, %16, %17, %18, %19, %20, %21, %22, %23, %24, %25, %26, %27, %28, %29, %30, %31, %32, %33, %34, %35, %36, %37, %38, %39, %40, %41, %42, %43, %44, %45, %46, %47, %48, %49, %50, %51, %52, %53, %54, %55, %56, %57, %58, %59, %60, %61, %62, %63, %64, %65, %66, %67, %68, %69, %70, %71, %72, %73, %74, %75, %76, %77, %78, %79, %80, %81, %82, %83, %84, %85, %86, %87, %88, %89, %90, %91, %92, %93, %94, %95, %96, %97, %98, %99, %100, %101, %102, %103, %104, %105, %106, %107, %108, %109, %110, %111}, %112, %113, p, 1, 1, 0, 1;\n}\n"
        : "+f"(d[0]), "+f"(d[1]), "+f"(d[2]), "+f"(d[3]), "+f"(d[4]), "+f"(d[5]), "+f"(d[6]), "+f"(d[7]), "+f"(d[8]), "+f"(d[9]), "+f"(d[10]), "+f"(d[11]), "+f"(d[12]), "+f"(d[13]), "+f"(d[14]), "+f"(d[15]), "+f"(d[16]), "+f"(d[17]), "+f"(d[18]), "+f"(d[19]), "+f"(d[20]), "+f"(d[21]), "+f"(d[22]), "+f"(d[23]), "+f"(d[24]), "+f"(d[25]), "+f"(d[26]), "+f"(d[27]), "+f"(d[28]), "+f"(d[29]), "+f"(d[30]), "+f"(d[31]), "+f"(d[32]), "+f"(d[33]), "+f"(d[34]), "+f"(d[35]), "+f"(d[36]), "+f"(d[37]), "+f"(d[38]), "+f"(d[39]), "+f"(d[40]), "+f"(d[41]), "+f"(d[42]), "+f"(d[43]), "+f"(d[44]), "+f"(d[45]), "+f"(d[46]), "+f"(d[47]), "+f"(d[48]), "+f"(d[49]), "+f"(d[50]), "+f"(d[51]), "+f"(d[52]), "+f"(d[53]), "+f"(d[54]), "+f"(d[55]), "+f"(d[56]), "+f"(d[57]), "+f"(d[58]), "+f"(d[59]), "+f"(d[60]), "+f"(d[61]), "+f"(d[62]), "+f"(d[63]), "+f"(d[64]), "+f"(d[65]), "+f"(d[66]), "+f"(d[67]), "+f"(d[68]), "+f"(d[69]), "+f"(d[70]), "+f"(d[71]), "+f"(d[72]), "+f"(d[73]), "+f"(d[74]), "+f"(d[75]), "+f"(d[76]), "+f"(d[77]), "+f"(d[78]), "+f"(d[79]), "+f"(d[80]), "+f"(d[81]), "+f"(d[82]), "+f"(d[83]), "+f"(d[84]), "+f"(d[85]), "+f"(d[86]), "+f"(d[87]), "+f"(d[88]), "+f"(d[89]), "+f"(d[90]), "+f"(d[91]), "+f"(d[92]), "+f"(d[93]), "+f"(d[94]), "+f"(d[95]), "+f"(d[96]), "+f"(d[97]), "+f"(d[98]), "+f"(d[99]), "+f"(d[100]), "+f"(d[101]), "+f"(d[102]), "+f"(d[103]), "+f"(d[104]), "+f"(d[105]), "+f"(d[106]), "+f"(d[107]), "+f"(d[108]), "+f"(d[109]), "+f"(d[110]), "+f"(d[111])
        : "l"(da), "l"(db), "r"(sd));
}
template <int SZ> __device__ __forceinline__ void wgmma_n56_ss(float (&d)[SZ], uint64_t da, uint64_t db, int sd) {
    asm volatile("{\n.reg .pred p;\nsetp.ne.b32 p, %30, 0;\n"
        "wgmma.mma_async.sync.aligned.m64n56k16.f32.bf16.bf16 {%0, %1, %2, %3, %4, %5, %6, %7, %8, %9, %10, %11, %12, %13, %14, %15, %16, %17, %18, %19, %20, %21, %22, %23, %24, %25, %26, %27}, %28, %29, p, 1, 1, 0, 1;\n}\n"
        : "+f"(d[0]), "+f"(d[1]), "+f"(d[2]), "+f"(d[3]), "+f"(d[4]), "+f"(d[5]), "+f"(d[6]), "+f"(d[7]), "+f"(d[8]), "+f"(d[9]), "+f"(d[10]), "+f"(d[11]), "+f"(d[12]), "+f"(d[13]), "+f"(d[14]), "+f"(d[15]), "+f"(d[16]), "+f"(d[17]), "+f"(d[18]), "+f"(d[19]), "+f"(d[20]), "+f"(d[21]), "+f"(d[22]), "+f"(d[23]), "+f"(d[24]), "+f"(d[25]), "+f"(d[26]), "+f"(d[27])
        : "l"(da), "l"(db), "r"(sd));
}

constexpr int MOD_BLOCKS = 84;
__global__ void __launch_bounds__(256) k_mod(const bf16* __restrict__ c, const bf16* __restrict__ w_mod) {
    __shared__ float red[8][32];
    __shared__ float sc[D_];
    pdl_launch();
    const int tid = threadIdx.x, warp = tid >> 5, lane = tid & 31;
    {
        const int tq = tid & 3, r = tid >> 2;
        const int col0 = blockIdx.x * 32 + tq * 8;
        uint4 cv = make_uint4(0, 0, 0, 0);
        if (tid < 56) cv = __ldg((const uint4*)c + tid);
        uint4 w[7];
#pragma unroll
        for (int i = 0; i < 7; i++) w[i] = __ldg((const uint4*)(w_mod + (size_t)(r + 64 * i) * (6 * D_) + col0));
        if (tid < 56) {
            const float v[8] = {bf16_lo(cv.x), bf16_hi(cv.x), bf16_lo(cv.y), bf16_hi(cv.y), bf16_lo(cv.z), bf16_hi(cv.z), bf16_lo(cv.w), bf16_hi(cv.w)};
#pragma unroll
            for (int k = 0; k < 8; k += 2) {
                float s0 = __fdividef(v[k], 1.0f + __expf(-v[k])), s1 = __fdividef(v[k + 1], 1.0f + __expf(-v[k + 1]));
                round2_bf16(s0, s1);
                sc[tid * 8 + k] = s0; sc[tid * 8 + k + 1] = s1;
            }
        }
        __syncthreads();
        float acc[8];
#pragma unroll
        for (int k = 0; k < 8; k++) acc[k] = 0.f;
#pragma unroll
        for (int i = 0; i < 7; i++) {
            float s = sc[r + 64 * i];
            acc[0] = fmaf(s, bf16_lo(w[i].x), acc[0]); acc[1] = fmaf(s, bf16_hi(w[i].x), acc[1]);
            acc[2] = fmaf(s, bf16_lo(w[i].y), acc[2]); acc[3] = fmaf(s, bf16_hi(w[i].y), acc[3]);
            acc[4] = fmaf(s, bf16_lo(w[i].z), acc[4]); acc[5] = fmaf(s, bf16_hi(w[i].z), acc[5]);
            acc[6] = fmaf(s, bf16_lo(w[i].w), acc[6]); acc[7] = fmaf(s, bf16_hi(w[i].w), acc[7]);
        }
#pragma unroll
        for (int k = 0; k < 8; k++) {
            acc[k] += __shfl_xor_sync(0xffffffffu, acc[k], 4);
            acc[k] += __shfl_xor_sync(0xffffffffu, acc[k], 8);
            acc[k] += __shfl_xor_sync(0xffffffffu, acc[k], 16);
        }
        if (lane < 4) {
#pragma unroll
            for (int k = 0; k < 8; k++) red[warp][lane * 8 + k] = acc[k];
        }
        __syncthreads();
        if (tid < 32) {
            float s = 0.f;
#pragma unroll
            for (int w2 = 0; w2 < 8; w2++) s += red[w2][tid];
            g_mod[blockIdx.x * 32 + tid] = round_bf16(s);
        }
    }
}

__device__ __forceinline__ void unpack8(const uint4& v, float* f) {
    f[0] = bf16_lo(v.x); f[1] = bf16_hi(v.x); f[2] = bf16_lo(v.y); f[3] = bf16_hi(v.y);
    f[4] = bf16_lo(v.z); f[5] = bf16_hi(v.z); f[6] = bf16_lo(v.w); f[7] = bf16_hi(v.w);
}
__device__ __forceinline__ uint4 pack8(const float* f) {
    uint4 v;
    v.x = pack_bf16(f[0], f[1]); v.y = pack_bf16(f[2], f[3]); v.z = pack_bf16(f[4], f[5]); v.w = pack_bf16(f[6], f[7]);
    return v;
}
__device__ __forceinline__ void row_stats(const float* f, bool act, float& mean, float& rstd) {
    (void)act;
    float s = 0.f, q = 0.f;
#pragma unroll
    for (int k = 0; k < 16; k++) { s += f[k]; q = fmaf(f[k], f[k], q); }
#pragma unroll
    for (int o = 16; o > 0; o >>= 1) {
        s += __shfl_xor_sync(0xffffffffu, s, o);
        q += __shfl_xor_sync(0xffffffffu, q, o);
    }
    mean = s * (1.0f / D_);
    const float var = fmaxf(fmaf(-mean, mean, q * (1.0f / D_)), 0.f);
    rstd = rsqrtf(var + LN_EPS);
}

__global__ void __launch_bounds__(512) k_ln(const bf16* __restrict__ x, const bf16* __restrict__ wq) {
    pdl_launch();
    const int warp = threadIdx.x >> 5, lane = threadIdx.x & 31;
    const int row = blockIdx.x * 16 + warp;
    const bool act = lane < 28;
    float f[16];
#pragma unroll
    for (int k = 0; k < 16; k++) f[k] = 0.f;
    if (act) {
        uint4 v0 = __ldg((const uint4*)(x + (size_t)row * D_) + lane);
        uint4 v1 = __ldg((const uint4*)(x + (size_t)row * D_) + lane + 28);
        unpack8(v0, f); unpack8(v1, f + 8);
    }
    if (act) {
        *((uint4*)(g_A + (size_t)row * D_) + lane) = make_uint4(0, 0, 0, 0);
        *((uint4*)(g_A + (size_t)row * D_) + lane + 28) = make_uint4(0, 0, 0, 0);
    }
    float mean, rstd;
    row_stats(f, act, mean, rstd);
    if (threadIdx.x == 0) {
        const int b = blockIdx.x;
        l2_prefetch((const char*)wq + (size_t)b * 28672, 28672);
    }
    pdl_wait();
    if (act) {
        const float* sa = g_mod;
        const float* ca = g_mod + D_;
        float o[16];
#pragma unroll
        for (int h = 0; h < 2; h++) {
            int c0 = (lane + 28 * h) * 8;
            float4 a0 = *(const float4*)(sa + c0), a1 = *(const float4*)(sa + c0 + 4);
            float4 b0 = *(const float4*)(ca + c0), b1 = *(const float4*)(ca + c0 + 4);
            float sv[8] = {a0.x, a0.y, a0.z, a0.w, a1.x, a1.y, a1.z, a1.w};
            float cv[8] = {b0.x, b0.y, b0.z, b0.w, b1.x, b1.y, b1.z, b1.w};
#pragma unroll
            for (int k = 0; k < 8; k++) {
                float n = (f[h * 8 + k] - mean) * rstd;
                o[h * 8 + k] = fmaf(n, 1.0f + cv[k], sv[k]);
            }
        }
        *((uint4*)(g_H + (size_t)row * D_) + lane) = pack8(o);
        *((uint4*)(g_H + (size_t)row * D_) + lane + 28) = pack8(o + 8);
    }
}

struct AttnMaps {
    CUtensorMap h;
    CUtensorMap wq;
    CUtensorMap k;
    CUtensorMap v;
    CUtensorMap wo4;
    CUtensorMap wo3;
    CUtensorMap park;
    CUtensorMap part;
    const bf16* x; const bf16* w1; const bf16* w2; const bf16* w3; const bf16* w4; const bf16* wo;
};

constexpr int SLOT = 16384;
constexpr int AT_NSLOT = 10;
constexpr int AT_QBUF = 0;
constexpr int AT_RING = 65536;
constexpr int AT_BAR = AT_RING + AT_NSLOT * SLOT;
constexpr int AT_SMEM = AT_BAR + 256;

#define LOAD3_SHARED(DST, MAP, FB, ROW, C2) tma_load_3d_mc((DST) + rank * 8192, MAP, FB, 0, (ROW) + rank * 16, C2)
#define LOAD2_SHARED(DST, MAP, FB, C0, ROW) tma_load_2d_mc((DST) + rank * 8192, MAP, FB, C0, (ROW) + rank * 64)

struct RingPos {
    uint32_t slot, phase;
    __device__ __forceinline__ void adv() { if (++slot == AT_NSLOT) { slot = 0; phase ^= 1; } }
};

__device__ __forceinline__ void colsum16(const bf16* w, int ld, int col0, int lane, float* out) {
    const int tq = lane & 1, r = lane >> 1;
    const bf16* src = w + col0 + tq * 8;
    float a[8];
#pragma unroll
    for (int k = 0; k < 8; k++) a[k] = 0.f;
#pragma unroll 4
    for (int i = r; i < D_; i += 16) {
        const uint4 v = __ldg((const uint4*)(src + (size_t)i * ld));
        a[0] += bf16_lo(v.x); a[1] += bf16_hi(v.x); a[2] += bf16_lo(v.y); a[3] += bf16_hi(v.y);
        a[4] += bf16_lo(v.z); a[5] += bf16_hi(v.z); a[6] += bf16_lo(v.w); a[7] += bf16_hi(v.w);
    }
#pragma unroll
    for (int k = 0; k < 8; k++) {
#pragma unroll
        for (int o = 2; o < 32; o <<= 1) a[k] += __shfl_xor_sync(0xffffffffu, a[k], o);
    }
    if (lane < 2) {
        float4* dstp = (float4*)(out + col0 + tq * 8);
        dstp[0] = make_float4(a[0], a[1], a[2], a[3]);
        dstp[1] = make_float4(a[4], a[5], a[6], a[7]);
    }
}

template <int NCOL, int SZ>
__device__ __forceinline__ void stage_tile(const float (&acc)[SZ], uint32_t buf, int wg, int warp_in_wg, int lane, float sc0, float sc1) {
    const int m = lane >> 3;
    const int r = lane & 7;
    const uint32_t rowaddr = buf + (uint32_t)(wg * 64 + warp_in_wg * 16 + (m & 1) * 8 + r) * 128;
#pragma unroll
    for (int j = 0; j < NCOL / 8; j += 2) {
        uint32_t p0 = pack_bf16(acc[4 * j + 0] * sc0, acc[4 * j + 1] * sc0);
        uint32_t p1 = pack_bf16(acc[4 * j + 2] * sc1, acc[4 * j + 3] * sc1);
        uint32_t p2 = pack_bf16(acc[4 * j + 4] * sc0, acc[4 * j + 5] * sc0);
        uint32_t p3 = pack_bf16(acc[4 * j + 6] * sc1, acc[4 * j + 7] * sc1);
        const int blk = j >> 3;
        const int chunk = (j & 7) + (m >> 1);
        stmatrix_x4(rowaddr + blk * 16384 + ((chunk ^ r) << 4), p0, p1, p2, p3);
    }
}

__device__ __forceinline__ uint32_t mul_bf16x2(uint32_t a, uint32_t b) {
    uint32_t r;
    asm("mul.rn.bf16x2 %0, %1, %2;" : "=r"(r) : "r"(a), "r"(b));
    return r;
}
template <int NCOL, int SZ>
__device__ __forceinline__ void stage_tile_colscale(const float (&acc)[SZ], uint32_t buf, int wg, int warp_in_wg, int lane, const uint32_t* sc) {
    const int m = lane >> 3;
    const int r = lane & 7;
    const uint32_t rowaddr = buf + (uint32_t)(wg * 64 + warp_in_wg * 16 + (m & 1) * 8 + r) * 128;
#pragma unroll
    for (int j = 0; j < NCOL / 8; j += 2) {
        const uint32_t g0 = sc[4 * j + (lane & 3)], g1 = sc[4 * j + 4 + (lane & 3)];
        const uint32_t p0 = mul_bf16x2(pack_bf16(acc[4 * j + 0], acc[4 * j + 1]), g0);
        const uint32_t p1 = mul_bf16x2(pack_bf16(acc[4 * j + 2], acc[4 * j + 3]), g0);
        const uint32_t p2 = mul_bf16x2(pack_bf16(acc[4 * j + 4], acc[4 * j + 5]), g1);
        const uint32_t p3 = mul_bf16x2(pack_bf16(acc[4 * j + 6], acc[4 * j + 7]), g1);
        const int blk = j >> 3;
        const int chunk = (j & 7) + (m >> 1);
        stmatrix_x4(rowaddr + blk * 16384 + ((chunk ^ r) << 4), p0, p1, p2, p3);
    }
}

__global__ void __cluster_dims__(2, 1, 1) __launch_bounds__(384, 1) k_attn(const __grid_constant__ AttnMaps maps) {
    extern __shared__ __align__(1024) uint8_t smem[];
    const uint32_t sbase = smem_u32(smem);
    const uint32_t qbuf = sbase + AT_QBUF;
    const uint32_t ring = sbase + AT_RING;
    const uint32_t bar_full = sbase + AT_BAR;
    const uint32_t bar_empty = bar_full + 8 * AT_NSLOT;
    const uint32_t bar_park = bar_empty + 8 * AT_NSLOT;

    const int warp = threadIdx.x >> 5, lane = threadIdx.x & 31;
    const int tile = blockIdx.x & 15;
    const int kvh = blockIdx.x >> 4;
    const int rank = blockIdx.x & 1;

    if (threadIdx.x == 0) {
        for (int i = 0; i < AT_NSLOT; i++) { mbar_init(bar_full + 8 * i, 1); mbar_init(bar_empty + 8 * i, 4); }
        mbar_init(bar_park, 2);
        fence_barrier_init();
        pdl_launch();
    }
    __syncthreads();
    cluster_sync();

    if (warp >= 8) {
        reg_dec<40>();
        if (warp == 8) {
            const bool el = elect_one();
            RingPos w{0, 0};
            int n = 0;
            if (el) {
                tma_prefetch_desc(&maps.wq); tma_prefetch_desc(&maps.h); tma_prefetch_desc(&maps.k); tma_prefetch_desc(&maps.v);
                tma_prefetch_desc(&maps.wo4); tma_prefetch_desc(&maps.wo3); tma_prefetch_desc(&maps.park); tma_prefetch_desc(&maps.part);
                const int h0 = kvh * 2;
#define AT_FIRST_W(S, KB, HF) { mbar_expect_tx(bar_full + 8 * (S), SLOT); LOAD3_SHARED(ring + (S) * SLOT, &maps.wq, bar_full + 8 * (S), (KB) * 64 + (HF) * 32, h0 * 4); }
#define AT_FIRST_H(S, KB) { mbar_expect_tx(bar_full + 8 * (S), SLOT); tma_load_2d(ring + (S) * SLOT, &maps.h, bar_full + 8 * (S), (KB) * 64, tile * 128); }
                AT_FIRST_W(0, 0, 0); AT_FIRST_W(2, 0, 1);
                pdl_wait();
                AT_FIRST_H(1, 0);
                AT_FIRST_W(3, 1, 0); AT_FIRST_H(4, 1); AT_FIRST_W(5, 1, 1);
                AT_FIRST_W(6, 2, 0); AT_FIRST_H(7, 2); AT_FIRST_W(8, 2, 1);
                AT_FIRST_W(9, 3, 0);
            }
            __syncwarp();
#define AT_ACQUIRE(BYTES)                                                       \
            const bool go = (n >= AT_NSLOT);                                    \
            if (go) mbar_wait(bar_empty + 8 * w.slot, w.phase ^ 1);             \
            const uint32_t dst = ring + w.slot * SLOT;                          \
            const uint32_t fb = bar_full + 8 * w.slot;                          \
            if (go && el) mbar_expect_tx(fb, BYTES);
#define AT_NEXT() w.adv(); n++;
            for (int hh = 0; hh < 2; hh++) {
                const int h = kvh * 2 + hh;
                for (int kb = 0; kb < 7; kb++) {
                    { AT_ACQUIRE(SLOT); if (go && el) LOAD3_SHARED(dst, &maps.wq, fb, kb * 64, h * 4); AT_NEXT(); }
                    { AT_ACQUIRE(SLOT); if (go && el) tma_load_2d(dst, &maps.h, fb, kb * 64, tile * 128); AT_NEXT(); }
                    { AT_ACQUIRE(SLOT); if (go && el) LOAD3_SHARED(dst, &maps.wq, fb, kb * 64 + 32, h * 4); AT_NEXT(); }
                }
                for (int c = 0; c < 4; c++) {
                    const int key0 = kvh * SK + (SK - WIN) + c * 128;
                    for (int d = 0; d < 4; d++) { AT_ACQUIRE(SLOT); if (go && el) LOAD2_SHARED(dst, &maps.k, fb, d * 64, key0); AT_NEXT(); }
                    for (int s = 0; s < 4; s++) { AT_ACQUIRE(SLOT); if (go && el) LOAD3_SHARED(dst, &maps.v, fb, key0 + s * 32, 0); AT_NEXT(); }
                }
            }
            mbar_wait(bar_park, 0);
            for (int p = 0; p < 2; p++) {
                const CUtensorMap* wo = p == 0 ? &maps.wo4 : &maps.wo3;
                const uint32_t bytes = p == 0 ? 16384u : 12288u;
                for (int kb = 0; kb < 8; kb++) {
                    const int krow = kvh * 512 + ((kb & 1) ? 0 : 256) + (kb >> 1) * 64;
                    { AT_ACQUIRE(bytes); if (go && el) LOAD3_SHARED(dst, wo, fb, krow, p * 4); AT_NEXT(); }
                    if (kb & 1) {
                        AT_ACQUIRE(SLOT);
                        if (go && el) {
                            tma_load_2d(dst, &maps.park, fb, (kb >> 1) * 64, blockIdx.x * 128);
                            tma_load_2d(dst + 8192, &maps.park, fb, (kb >> 1) * 64, blockIdx.x * 128 + 64);
                        }
                        AT_NEXT();
                    }
                    { AT_ACQUIRE(bytes); if (go && el) LOAD3_SHARED(dst, wo, fb, krow + 32, p * 4); AT_NEXT(); }
                }
            }
        } else if (warp == 11) {
            mbar_wait(bar_park, 0);
            if (blockIdx.x < F_ / 16) colsum16(maps.w3, F_, blockIdx.x * 16, lane, g_colsum3);
            if (blockIdx.x >= 100) colsum16(maps.w1, D_, (blockIdx.x - 100) * 16, lane, g_colsum1);
            if (lane == 0) {
                const int b = blockIdx.x;
                l2_prefetch((const char*)maps.wo + (size_t)b * 28672, 28672);
                l2_prefetch((const char*)maps.x + (size_t)b * 14336, 14336);
                l2_prefetch((const char*)maps.w1 + (size_t)b * 3136, 3136);
                l2_prefetch((const char*)maps.w2 + (size_t)b * 3136, 3136);
                l2_prefetch((const char*)maps.w3 + (size_t)b * 12544, 12544);
                l2_prefetch((const char*)maps.w4 + (size_t)b * 12544, 12544);
                if (b == 0) l2_prefetch(g_mod, 6 * D_ * 4);
            }
        }
    } else {
        reg_inc<232>();
        const int wg = __shfl_sync(0xffffffffu, warp >> 2, 0);
        const int wq_ = warp & 3;
        const bool sig = (threadIdx.x & 127) == 0;
        const bool rsig = (wq_ < 2) && (lane == 0);
        const uint32_t rel_base = map_cluster(bar_empty, wq_ & 1);
        const int bar_me = 2 + wg, bar_other = 2 + (wg ^ 1), bar_wg = 4 + wg;
        if (wg == 1) named_arrive(2, 256);

        float acc[128];
        RingPos rd{0, 0};
        uint32_t rel = 0;
#define AT_RELEASE(CNT)                                                                       \
        {                                                                                     \
            _Pragma("unroll") for (int _i = 0; _i < (CNT); _i++) {                            \
                if (rsig) mbar_arrive_cluster(rel_base + 8 * rel);                            \
                if (++rel == AT_NSLOT) rel = 0;                                               \
            }                                                                                 \
        }
        const uint32_t ring16 = (ring & 0x3FFFF) >> 4;
        const uint64_t descK = make_desc(0, 16, 1024);
        const uint64_t descMN = make_desc(0, 2048, 1024);
        const float cs = 0.0625f * 1.4426950408889634f;
        const uint64_t dq = descK + (((qbuf & 0x3FFFF) >> 4) + wg * 512);
        float i0 = 0.f, i1 = 0.f;

        for (int hh = 0; hh < 2; hh++) {
            const int nf = (hh == 0) ? 1 : 2;
#pragma unroll 1
            for (int kb = 0; kb < 7; kb++) {
                const bool single = kb <= 4 && kb >= (nf == 1 ? 0 : 2);
                const uint32_t sb1 = rd.slot; mbar_wait(bar_full + 8 * rd.slot, rd.phase); rd.adv();
                const uint32_t sa = rd.slot; mbar_wait(bar_full + 8 * rd.slot, rd.phase); rd.adv();
                const uint32_t sb2 = rd.slot; mbar_wait(bar_full + 8 * rd.slot, rd.phase); rd.adv();
                if (kb == 0 || kb == 5 || single) named_sync(bar_me, 256);
                const uint64_t da = descK + (ring16 + sa * 1024 + wg * 512);
                const uint64_t db1 = descMN + (ring16 + sb1 * 1024);
                const uint64_t db2 = descMN + (ring16 + sb2 * 1024);
                wg_fence();
                wgmma_n256_ss(acc, da + 0, db1, kb > 0);
                wgmma_n256_ss(acc, da + 2, db1 + 512, 1);
                wg_commit();
                wgmma_n256_ss(acc, da + 4, db2, 1);
                wgmma_n256_ss(acc, da + 6, db2 + 512, 1);
                wg_commit();
                const bool pair_end = (kb == 1 && !single) || kb == 6;
                if (single || pair_end) named_arrive(bar_other, 256);
                if (single) { wg_wait<1>(); AT_RELEASE(1); wg_wait<0>(); AT_RELEASE(2); }
                if (pair_end) {
                    wg_wait<3>(); AT_RELEASE(1);
                    wg_wait<2>(); AT_RELEASE(2);
                    wg_wait<1>(); AT_RELEASE(1);
                    if (kb == 1) { wg_wait<0>(); AT_RELEASE(2); }
                }
            }
            wg_wait<0>();
            fence_regs(acc);
            AT_RELEASE(2);
            if (hh == 1) {
                if (sig) { bulk_wait0(); mbar_arrive(bar_park); }
                named_sync(bar_wg, 128);
            }
            stage_tile<256>(acc, qbuf, wg, wq_, lane, 1.0f, 1.0f);
            fence_proxy_async();
            named_sync(bar_wg, 128);

            float m0 = -INFINITY, m1 = -INFINITY, l0 = 0.f, l1 = 0.f;
            uint32_t p[32];
#pragma unroll 1
            for (int c = 0; c < 5; c++) {
                mbar_wait(bar_full + 8 * rd.slot, rd.phase);
                if (c > 0) fence_regs(acc);
                named_sync(bar_me, 256);
                if (c > 0) {
                    wg_fence();
#pragma unroll
                    for (int sv = 0; sv < 4; sv++) {
                        if (sv > 0) mbar_wait(bar_full + 8 * rd.slot, rd.phase);
                        const uint64_t db = descMN + (ring16 + rd.slot * 1024);
                        rd.adv();
                        wgmma_n256_rs(acc, p[8 * sv + 0], p[8 * sv + 1], p[8 * sv + 2], p[8 * sv + 3], db, (c - 1 | sv) != 0);
                        wgmma_n256_rs(acc, p[8 * sv + 4], p[8 * sv + 5], p[8 * sv + 6], p[8 * sv + 7], db + 512, 1);
                    }
                    wg_commit();
                    if (c == 4) {
                        named_arrive(bar_other, 256);
                        wg_wait<0>();
                        fence_regs(acc);
                        AT_RELEASE(4);
                        break;
                    }
                    mbar_wait(bar_full + 8 * rd.slot, rd.phase);
                    wg_wait<0>();
                    fence_regs(acc);
                }
                float s[64];
                {
                    wg_fence();
#pragma unroll
                    for (int d = 0; d < 4; d++) {
                        if (d > 0) mbar_wait(bar_full + 8 * rd.slot, rd.phase);
                        const uint64_t db = descK + (ring16 + rd.slot * 1024);
                        rd.adv();
#pragma unroll
                        for (int t = 0; t < 4; t++) wgmma_n128_ss(s, dq + d * 1024 + t * 2, db + t * 2, (d | t) != 0);
                        if (d == 0 && c > 0) AT_RELEASE(4);
                    }
                    wg_commit();
                    named_arrive(bar_other, 256);
                    wg_wait<0>();
                    fence_regs(s);
                    AT_RELEASE(4);
                }
                float mx0, mx1;
                {
                    float u0 = fmaxf(s[0], s[1]), u1 = fmaxf(s[4], s[5]), u2 = fmaxf(s[8], s[9]), u3 = fmaxf(s[12], s[13]);
                    float v0 = fmaxf(s[2], s[3]), v1 = fmaxf(s[6], s[7]), v2 = fmaxf(s[10], s[11]), v3 = fmaxf(s[14], s[15]);
#pragma unroll
                    for (int j = 4; j < 16; j += 4) {
                        u0 = fmaxf(u0, fmaxf(s[4 * j + 0], s[4 * j + 1])); v0 = fmaxf(v0, fmaxf(s[4 * j + 2], s[4 * j + 3]));
                        u1 = fmaxf(u1, fmaxf(s[4 * j + 4], s[4 * j + 5])); v1 = fmaxf(v1, fmaxf(s[4 * j + 6], s[4 * j + 7]));
                        u2 = fmaxf(u2, fmaxf(s[4 * j + 8], s[4 * j + 9])); v2 = fmaxf(v2, fmaxf(s[4 * j + 10], s[4 * j + 11]));
                        u3 = fmaxf(u3, fmaxf(s[4 * j + 12], s[4 * j + 13])); v3 = fmaxf(v3, fmaxf(s[4 * j + 14], s[4 * j + 15]));
                    }
                    mx0 = fmaxf(fmaxf(u0, u1), fmaxf(u2, u3));
                    mx1 = fmaxf(fmaxf(v0, v1), fmaxf(v2, v3));
                }
                mx0 = fmaxf(mx0, __shfl_xor_sync(0xffffffffu, mx0, 1));
                mx1 = fmaxf(mx1, __shfl_xor_sync(0xffffffffu, mx1, 1));
                mx0 = fmaxf(mx0, __shfl_xor_sync(0xffffffffu, mx0, 2));
                mx1 = fmaxf(mx1, __shfl_xor_sync(0xffffffffu, mx1, 2));
                {
                    const float mn0 = fmaxf(m0, mx0), mn1 = fmaxf(m1, mx1);
                    const float a0 = ex2f((m0 - mn0) * cs), a1 = ex2f((m1 - mn1) * cs);
                    m0 = mn0; m1 = mn1;
                    l0 *= a0; l1 *= a1;
                    if (c > 0) {
#pragma unroll
                        for (int j = 0; j < 32; j++) {
                            acc[4 * j + 0] *= a0; acc[4 * j + 1] *= a0;
                            acc[4 * j + 2] *= a1; acc[4 * j + 3] *= a1;
                        }
                    }
                }
                const float mc0 = -m0 * cs, mc1 = -m1 * cs;
                float r0 = 0.f, r1 = 0.f;
#pragma unroll
                for (int j = 0; j < 16; j++) {
                    float e0 = ex2f(fmaf(s[4 * j + 0], cs, mc0));
                    float e1 = ex2f(fmaf(s[4 * j + 1], cs, mc0));
                    float e2 = ex2f(fmaf(s[4 * j + 2], cs, mc1));
                    float e3 = ex2f(fmaf(s[4 * j + 3], cs, mc1));
                    r0 += e0 + e1;
                    r1 += e2 + e3;
                    p[2 * j] = pack_bf16(e0, e1);
                    p[2 * j + 1] = pack_bf16(e2, e3);
                }
                l0 += r0;
                l1 += r1;
            }
            l0 += __shfl_xor_sync(0xffffffffu, l0, 1);
            l1 += __shfl_xor_sync(0xffffffffu, l1, 1);
            l0 += __shfl_xor_sync(0xffffffffu, l0, 2);
            l1 += __shfl_xor_sync(0xffffffffu, l1, 2);
            i0 = __frcp_rn(l0); i1 = __frcp_rn(l1);
            if (hh == 0) {
                stage_tile<256>(acc, qbuf, wg, wq_, lane, i0, i1);
                fence_proxy_async();
                named_sync(bar_wg, 128);
                if (sig) {
#pragma unroll
                    for (int b = 0; b < 4; b++)
                        tma_store_2d(&maps.park, qbuf + b * 16384 + wg * 8192, b * 64, blockIdx.x * 128 + wg * 64);
                    bulk_commit();
                }
            }
        }
        uint32_t o1p[64];
#pragma unroll
        for (int j = 0; j < 32; j++) {
            o1p[2 * j] = pack_bf16(acc[4 * j] * i0, acc[4 * j + 1] * i0);
            o1p[2 * j + 1] = pack_bf16(acc[4 * j + 2] * i1, acc[4 * j + 3] * i1);
        }
        fence_regs(o1p);

#define AT_OP_RS(WG_RS, J, FIRSTMMA)                                                             \
            {                                                                                    \
                const uint32_t sb1 = rd.slot; mbar_wait(bar_full + 8 * rd.slot, rd.phase); rd.adv();  \
                const uint32_t sb2 = rd.slot; mbar_wait(bar_full + 8 * rd.slot, rd.phase); rd.adv();  \
                if (turn_) named_sync(bar_me, 256);                                              \
                const uint64_t db1 = descMN + (ring16 + sb1 * 1024);                             \
                const uint64_t db2 = descMN + (ring16 + sb2 * 1024);                             \
                wg_fence();                                                                      \
                WG_RS(acc, o1p[16 * (J) + 0], o1p[16 * (J) + 1], o1p[16 * (J) + 2], o1p[16 * (J) + 3], db1, !(FIRSTMMA));  \
                WG_RS(acc, o1p[16 * (J) + 4], o1p[16 * (J) + 5], o1p[16 * (J) + 6], o1p[16 * (J) + 7], db1 + 512, 1);      \
                WG_RS(acc, o1p[16 * (J) + 8], o1p[16 * (J) + 9], o1p[16 * (J) + 10], o1p[16 * (J) + 11], db2, 1);          \
                WG_RS(acc, o1p[16 * (J) + 12], o1p[16 * (J) + 13], o1p[16 * (J) + 14], o1p[16 * (J) + 15], db2 + 512, 1);  \
                wg_commit();                                                                     \
            }
#define AT_OP_SS(WG_SS)                                                                          \
            {                                                                                    \
                const uint32_t sb1 = rd.slot; mbar_wait(bar_full + 8 * rd.slot, rd.phase); rd.adv();  \
                const uint32_t sa = rd.slot; mbar_wait(bar_full + 8 * rd.slot, rd.phase); rd.adv();   \
                const uint32_t sb2 = rd.slot; mbar_wait(bar_full + 8 * rd.slot, rd.phase); rd.adv();  \
                if (turn_) named_sync(bar_me, 256);                                              \
                const uint64_t da = descK + (ring16 + sa * 1024 + wg * 512);                     \
                const uint64_t db1 = descMN + (ring16 + sb1 * 1024);                             \
                const uint64_t db2 = descMN + (ring16 + sb2 * 1024);                             \
                wg_fence();                                                                      \
                WG_SS(acc, da + 0, db1, 1);                                                      \
                WG_SS(acc, da + 2, db1 + 512, 1);                                                \
                WG_SS(acc, da + 4, db2, 1);                                                      \
                WG_SS(acc, da + 6, db2 + 512, 1);                                                \
                wg_commit();                                                                     \
            }
#define AT_OP_REL(KB) { if ((KB) & 1) { AT_RELEASE(3); } else { AT_RELEASE(2); } }
#define AT_OUTPROJ(WG_SS, WG_RS, FIRST, NF)                                                      \
        _Pragma("unroll") for (int kb = 0; kb < 8; kb++) {                                       \
            const bool turn_ = kb == 0 || (kb >= (NF) && kb < 7);                                \
            if (kb & 1) { AT_OP_SS(WG_SS) } else { AT_OP_RS(WG_RS, kb >> 1, kb == 0) }          \
            const bool last_in_turn = (kb >= (NF) - 1 && kb < 6) || kb == 7;                     \
            if (last_in_turn && !(kb == 7 && (FIRST) == 0 && wg == 1)) named_arrive(bar_other, 256);  \
            if (kb == (NF) - 1) {                                                                \
                if ((NF) == 3) { wg_wait<2>(); AT_OP_REL(0); }                                   \
                wg_wait<1>(); AT_OP_REL((NF) - 2);                                               \
                wg_wait<0>(); AT_OP_REL((NF) - 1);                                               \
            } else if (kb >= (NF) && kb < 6) {                                                   \
                wg_wait<0>(); AT_OP_REL(kb);                                                     \
            } else if (kb == 7) {                                                                \
                wg_wait<1>(); AT_OP_REL(6);                                                      \
                wg_wait<0>();  fence_regs(acc); AT_OP_REL(7);                             \
            }                                                                                    \
        }
        const int prow = tile * 128 + wg * 64;
        {
            AT_OUTPROJ(wgmma_n256_ss, wgmma_n256_rs, 1, 2);
            stage_tile<256>(acc, qbuf, wg, wq_, lane, 1.0f, 1.0f);
            fence_proxy_async();
            named_sync(bar_wg, 128);
            if (sig) {
#pragma unroll
                for (int b = 0; b < 4; b++) tma_reduce_add_2d(&maps.part, qbuf + b * 16384 + wg * 8192, b * 64, prow);
                bulk_commit();
            }
        }
        {
            AT_OUTPROJ(wgmma_n192_ss, wgmma_n192_rs, 0, 3);
            if (sig) bulk_wait_read0();
            named_sync(bar_wg, 128);
            stage_tile<192>(acc, qbuf, wg, wq_, lane, 1.0f, 1.0f);
            fence_proxy_async();
            named_sync(bar_wg, 128);
            if (sig) {
#pragma unroll
                for (int b = 0; b < 3; b++) tma_reduce_add_2d(&maps.part, qbuf + b * 16384 + wg * 8192, 256 + b * 64, prow);
                bulk_commit();
                bulk_wait_read0();
            }
        }
    }
    __syncwarp();
    cluster_sync();
}

__global__ void __maxnreg__(96) k_t0(const bf16* __restrict__ x, bf16* __restrict__ out) {
    pdl_launch();
    const int warp = threadIdx.x >> 5, lane = threadIdx.x & 31;
    const int row = blockIdx.x * 16 + warp;
    const bool act = lane < 28;
    const int l = act ? lane : 0;
    const uint4 xv0 = __ldg((const uint4*)(x + (size_t)row * D_) + l);
    const uint4 xv1 = __ldg((const uint4*)(x + (size_t)row * D_) + l + 28);
    if (blockIdx.x == 0 && threadIdx.x < 14 * 6) {
        const int seg = threadIdx.x / 14, ch = threadIdx.x % 14;
        const int r = seg == 0 ? 0 : seg == 1 ? S_ - 1 : seg == 2 ? 0 : seg == 3 ? 1 : seg == 4 ? S_ - 2 : S_ - 1;
        const int g = seg == 0 ? 0 : seg == 1 ? 1 : seg < 4 ? 2 : 3;
        *((uint4*)(g_G + (size_t)(r + 2) * D_ + g * 112) + ch) = make_uint4(0, 0, 0, 0);
    }
    float4 mv[16];
#pragma unroll
    for (int v = 0; v < 4; v++)
#pragma unroll
        for (int h = 0; h < 2; h++)
#pragma unroll
            for (int q = 0; q < 2; q++) {
                const float* p = g_mod + (2 + v) * D_ + (l + 28 * h) * 8 + 4 * q;
                asm volatile("ld.relaxed.cta.global.v4.f32 {%0, %1, %2, %3}, [%4];"
                             : "=f"(mv[v * 4 + h * 2 + q].x), "=f"(mv[v * 4 + h * 2 + q].y), "=f"(mv[v * 4 + h * 2 + q].z), "=f"(mv[v * 4 + h * 2 + q].w) : "l"(p) : "memory");
            }
    pdl_wait();
    const uint4 av0 = __ldcg((const uint4*)(g_A + (size_t)row * D_) + l), av1 = __ldcg((const uint4*)(g_A + (size_t)row * D_) + l + 28);
    const float* mf = (const float*)mv;
    float f[16];
    uint4 x1p0, x1p1;
    {
        float a[16];
        unpack8(av0, a); unpack8(av1, a + 8);
        unpack8(xv0, f); unpack8(xv1, f + 8);
#pragma unroll
        for (int k = 0; k < 16; k++) f[k] = fmaf(mf[k], a[k], f[k]);
        const uint4 o0 = pack8(f), o1 = pack8(f + 8);
        x1p0 = o0; x1p1 = o1;
        unpack8(o0, f); unpack8(o1, f + 8);
        if (!act) {
#pragma unroll
            for (int k = 0; k < 16; k++) f[k] = 0.f;
        }
    }
    float mean, rstd;
    row_stats(f, act, mean, rstd);
    {
#pragma unroll
        for (int k = 0; k < 16; k++) f[k] = fmaf((f[k] - mean) * rstd, 1.0f + mf[32 + k], mf[16 + k]);
        const uint4 o0 = pack8(f), o1 = pack8(f + 8);
        if (act) {
            *((uint4*)(g_hb + (size_t)row * D_) + lane) = o0;
            *((uint4*)(g_hb + (size_t)row * D_) + lane + 28) = o1;
        }
        unpack8(o0, f); unpack8(o1, f + 8);
        {
            float b[16];
            unpack8(x1p0, b); unpack8(x1p1, b + 8);
#pragma unroll
            for (int k = 0; k < 16; k++) b[k] = fmaf(mf[48 + k], f[k], b[k]);
            if (act) {
                *((uint4*)(out + (size_t)row * D_) + lane) = pack8(b);
                *((uint4*)(out + (size_t)row * D_) + lane + 28) = pack8(b + 8);
            }
        }
        if (!act) {
#pragma unroll
            for (int k = 0; k < 16; k++) f[k] = 0.f;
        }
    }
    row_stats(f, act, mean, rstd);
    if (lane == 0) g_hstat[row] = make_float2(mean, rstd);
}

constexpr int T2_NPRE = 4;
struct SmallMaps {
    CUtensorMap a;
    CUtensorMap w;
    CUtensorMap out;
    CUtensorMap res;
    CUtensorMap fin;
};
constexpr int SG_A = 0;
constexpr int SG_B = 7 * 8192;
constexpr int SG_STG = SG_B + 14 * 8192;
constexpr int SG_STG2 = SG_STG + 2 * 7168;
constexpr int SG_BAR = SG_STG2 + 2 * 7168;
constexpr int SG_SMEM = SG_BAR + 256;

#define SG_LOAD_B(KB) tma_load_2d_mc(sbase + SG_B + (rank * 7 + (KB)) * 8192, &maps.w, barB + 8 * (KB), col0 + rank * 56, (KB) * 64)
template <int MODE>
__global__ void __cluster_dims__(2, 1, 1) __launch_bounds__(256, 1) k_small(const __grid_constant__ SmallMaps maps) {
    extern __shared__ __align__(1024) uint8_t smem[];
    const uint32_t sbase = smem_u32(smem);
    const uint32_t barA = sbase + SG_BAR;
    const uint32_t barB = barA + 56;
    const uint32_t barR = barB + 56;
    const int warp = __shfl_sync(0xffffffffu, threadIdx.x >> 5, 0), lane = threadIdx.x & 31;
    const int wg = warp >> 2;
    const int rank = blockIdx.x & 1;
    const int rt = ((blockIdx.x >> 1) & 15) * 2 + rank;
    const int cg = blockIdx.x >> 5;
    const int col0 = cg * 112;
    if (warp == 0) {
        if (elect_one()) {
            tma_prefetch_desc(&maps.w); tma_prefetch_desc(&maps.a);
            for (int i = 0; i < 7; i++) { mbar_init(barA + 8 * i, 1); mbar_init(barB + 8 * i, 1); }
            mbar_init(barR, 1);
            fence_barrier_init();
            pdl_launch();
#pragma unroll
            for (int kb = 0; kb < 7; kb++) mbar_expect_tx(barB + 8 * kb, 2 * 8192);
            tma_prefetch_desc(&maps.out);
            if (MODE == 1) { tma_prefetch_desc(&maps.res); tma_prefetch_desc(&maps.fin); }
        }
        __syncwarp();
    }
    cluster_sync();
    if (warp == 0) {
        if (elect_one()) {
            constexpr int NPRE = MODE == 0 ? 7 : T2_NPRE;
#pragma unroll
            for (int kb = 0; kb < NPRE; kb++) SG_LOAD_B(kb);
            pdl_wait();
#pragma unroll
            for (int kb = 0; kb < 7; kb++) {
                if (kb >= NPRE) SG_LOAD_B(kb);
                mbar_expect_tx(barA + 8 * kb, 8192);
                tma_load_2d(sbase + SG_A + kb * 8192, &maps.a, barA + 8 * kb, kb * 64, rt * 64);
            }
            if (MODE == 1) {
                mbar_expect_tx(barR, 2 * 7168);
#pragma unroll
                for (int w = 0; w < 2; w++) tma_load_2d(sbase + SG_STG + w * 7168, &maps.res, barR, col0 + w * 56, rt * 64);
            }
        }
        __syncwarp();
    }
    float acc[28];
    const uint32_t a16 = ((sbase + SG_A) & 0x3FFFF) >> 4;
    const uint32_t b16 = ((sbase + SG_B + wg * 7 * 8192) & 0x3FFFF) >> 4;
    const uint64_t dA = make_desc(0, 16, 1024) + a16;
    const uint64_t dB = make_desc(0, 8192, 1024) + b16;
    float2 st0 = make_float2(0.f, 0.f), st1 = st0, cs[7];
#pragma unroll
    for (int kb = 0; kb < 7; kb++) {
        mbar_wait(barB + 8 * kb, 0);
        mbar_wait(barA + 8 * kb, 0);
        if (MODE == 1 && kb == 0) {
#pragma unroll
            for (int j = 0; j < 7; j++)
                asm volatile("ld.relaxed.cta.global.v2.f32 {%0, %1}, [%2];" : "=f"(cs[j].x), "=f"(cs[j].y)
                             : "l"(g_mod + 5 * D_ + col0 + wg * 56 + j * 8 + (lane & 3) * 2) : "memory");
        }
        if (MODE == 0 && kb == 0) {
            const int rr = rt * 64 + (warp & 3) * 16 + (lane >> 2);
            asm volatile("ld.relaxed.gpu.global.v2.f32 {%0, %1}, [%2];" : "=f"(st0.x), "=f"(st0.y) : "l"(g_hstat + rr) : "memory");
            asm volatile("ld.relaxed.gpu.global.v2.f32 {%0, %1}, [%2];" : "=f"(st1.x), "=f"(st1.y) : "l"(g_hstat + rr + 8) : "memory");
#pragma unroll
            for (int j = 0; j < 7; j++)
                asm volatile("ld.relaxed.cta.global.v2.f32 {%0, %1}, [%2];" : "=f"(cs[j].x), "=f"(cs[j].y)
                             : "l"(g_colsum1 + col0 + wg * 56 + j * 8 + (lane & 3) * 2) : "memory");
        }
        wg_fence();
#pragma unroll
        for (int t = 0; t < 4; t++) wgmma_n56_ss(acc, dA + kb * 512 + t * 2, dB + kb * 512 + t * 128, (kb | t) != 0);
        wg_commit();
    }
    asm volatile("barrier.cluster.arrive.relaxed.aligned;" ::: "memory");
    if (MODE == 1) mbar_wait(barR, 0);
    wg_wait<0>();
    fence_regs(acc);
    uint8_t* stg = smem + SG_STG + wg * 7168;
    const int r0 = (warp & 3) * 16 + (lane >> 2);
    const int cq = (lane & 3) * 2;
    float y0[14], y1[14];
#pragma unroll
    for (int j = 0; j < 7; j++) {
        uint32_t* p0 = (uint32_t*)(stg + r0 * 112 + (j * 8 + cq) * 2);
        uint32_t* p1 = (uint32_t*)(stg + (r0 + 8) * 112 + (j * 8 + cq) * 2);
        if (MODE == 0) {
            const float z0 = st0.y * fmaf(-st0.x, cs[j].x, acc[4 * j]), z1 = st0.y * fmaf(-st0.x, cs[j].y, acc[4 * j + 1]);
            const float z2 = st1.y * fmaf(-st1.x, cs[j].x, acc[4 * j + 2]), z3 = st1.y * fmaf(-st1.x, cs[j].y, acc[4 * j + 3]);
            *p0 = pack_bf16(gelu_tanh(z0), gelu_tanh(z1));
            *p1 = pack_bf16(gelu_tanh(z2), gelu_tanh(z3));
        } else {
            const uint32_t h0 = *p0, h1 = *p1;
            const uint32_t q0 = pack_bf16(bf16_lo(h0) + acc[4 * j], bf16_hi(h0) + acc[4 * j + 1]);
            const uint32_t q1 = pack_bf16(bf16_lo(h1) + acc[4 * j + 2], bf16_hi(h1) + acc[4 * j + 3]);
            *p0 = q0; *p1 = q1;
            y0[2 * j] = bf16_lo(q0); y0[2 * j + 1] = bf16_hi(q0);
            y1[2 * j] = bf16_lo(q1); y1[2 * j + 1] = bf16_hi(q1);
            *(uint32_t*)((uint8_t*)p0 + 2 * 7168) = pack_bf16(cs[j].x * acc[4 * j], cs[j].y * acc[4 * j + 1]);
            *(uint32_t*)((uint8_t*)p1 + 2 * 7168) = pack_bf16(cs[j].x * acc[4 * j + 2], cs[j].y * acc[4 * j + 3]);
        }
    }
    fence_proxy_async();
    if (wg == 0) named_sync_imm<1, 128>(); else named_sync_imm<2, 128>();
    if ((threadIdx.x & 127) == 0) {
        const int shift = MODE == 0 ? (cg == 0 ? 3 : cg == 1 ? 1 : cg == 2 ? 4 : 0) : 0;
        tma_store_2d(&maps.out, smem_u32(stg), col0 + wg * 56, rt * 64 + shift);
        if (MODE == 1) tma_reduce_add_2d(&maps.fin, smem_u32(stg) + 2 * 7168, col0 + wg * 56, rt * 64);
        bulk_commit();
    }
    if (MODE == 1) {
        float s0 = 0.f, s1 = 0.f;
#pragma unroll
        for (int k = 0; k < 14; k++) { s0 += y0[k]; s1 += y1[k]; }
        s0 += __shfl_xor_sync(0xffffffffu, s0, 1); s1 += __shfl_xor_sync(0xffffffffu, s1, 1);
        s0 += __shfl_xor_sync(0xffffffffu, s0, 2); s1 += __shfl_xor_sync(0xffffffffu, s1, 2);
        s0 *= (1.0f / 56); s1 *= (1.0f / 56);
        float q0 = 0.f, q1 = 0.f;
#pragma unroll
        for (int k = 0; k < 14; k++) { const float d0 = y0[k] - s0, d1 = y1[k] - s1; q0 = fmaf(d0, d0, q0); q1 = fmaf(d1, d1, q1); }
        q0 += __shfl_xor_sync(0xffffffffu, q0, 1); q1 += __shfl_xor_sync(0xffffffffu, q1, 1);
        q0 += __shfl_xor_sync(0xffffffffu, q0, 2); q1 += __shfl_xor_sync(0xffffffffu, q1, 2);
        if ((lane & 3) == 0) {
            g_ystat[(cg * 2 + wg) * S_ + rt * 64 + r0] = make_float2(s0, q0);
            g_ystat[(cg * 2 + wg) * S_ + rt * 64 + r0 + 8] = make_float2(s1, q1);
        }
    }
    if ((threadIdx.x & 127) == 0) {
        bulk_wait_read0();
    }
    __syncwarp();
    asm volatile("barrier.cluster.wait.aligned;" ::: "memory");
}

struct MlpMaps {
    CUtensorMap y;
    CUtensorMap w3;
    CUtensorMap w4a;
    CUtensorMap w4b;
    CUtensorMap part;
};
constexpr int ML_PREG = 40;
constexpr int ML_CREG = 232;
constexpr int ML_LAST = 2;
constexpr int ML_NPRE = 4;
constexpr int ML_NSLOT = 10;
constexpr int ML_STG = 0;
constexpr int ML_RING = 65536;
constexpr int ML_CS = ML_RING + ML_NSLOT * SLOT;
constexpr int ML_GB = ML_CS + 2 * 896;
constexpr int ML_BAR = ML_GB + 896;
constexpr int ML_SMEM = ML_BAR + 192;

__global__ void __cluster_dims__(2, 1, 1) __launch_bounds__(384, 1) k_mlp(const __grid_constant__ MlpMaps maps) {
    extern __shared__ __align__(1024) uint8_t smem[];
    const uint32_t sbase = smem_u32(smem);
    const uint32_t stg = sbase + ML_STG;
    const uint32_t ring = sbase + ML_RING;
    const uint32_t bar_full = sbase + ML_BAR;
    const uint32_t bar_empty = bar_full + 8 * ML_NSLOT;
    const uint32_t bar_a = bar_empty + 8 * ML_NSLOT;
    const int warp = threadIdx.x >> 5, lane = threadIdx.x & 31;
    const int tile = blockIdx.x & 15;
    const int fs = blockIdx.x >> 4;
    const int rank = blockIdx.x & 1;
    if (threadIdx.x == 0) {
        for (int i = 0; i < ML_NSLOT; i++) { mbar_init(bar_full + 8 * i, 1); mbar_init(bar_empty + 8 * i, 4); }
        for (int i = 0; i < 4; i++) mbar_init(bar_a + 8 * i, 1);
        fence_barrier_init();
        pdl_launch();
    }
    if (threadIdx.x == 256) { tma_prefetch_desc(&maps.w3); tma_prefetch_desc(&maps.y); tma_prefetch_desc(&maps.w4a); tma_prefetch_desc(&maps.w4b); tma_prefetch_desc(&maps.part); }
    __syncthreads();
    cluster_sync();
    if (warp >= 8) {
        reg_dec<ML_PREG>();
        if (warp == 8) {
            const bool el = elect_one();
#define ML_LOAD_W3(DST, FB, KS)                                                                                   \
            {                \
                mbar_expect_tx(FB, 16384);                                                                        \
                tma_load_2d_mc((DST) + rank * 8192, &maps.w3, FB, fs * 224 + rank * 128, (KS) * 32);              \
                tma_load_2d_mc((DST) + rank * 8192 + 4096, &maps.w3, FB, fs * 224 + rank * 128 + 64, (KS) * 32);  \
            }
#define ML_LOAD_Y(DST, FB, KB) { mbar_expect_tx(FB, 16384); tma_load_2d(DST, &maps.y, FB, (KB) * 64, tile * 128); }
            if (el) {
#pragma unroll
                for (int i = 0; i < ML_NPRE; i++) ML_LOAD_W3(ring + i * SLOT, bar_full + 8 * i, i);
                pdl_wait();
#pragma unroll
                for (int kb = 0; kb < 4; kb++) {
                    ML_LOAD_Y(stg + kb * 16384, bar_a + 8 * kb, kb);
                    if (2 * kb >= ML_NPRE) ML_LOAD_W3(ring + (2 * kb) * SLOT, bar_full + 8 * (2 * kb), 2 * kb);
                    if (2 * kb + 1 >= ML_NPRE) ML_LOAD_W3(ring + (2 * kb + 1) * SLOT, bar_full + 8 * (2 * kb + 1), 2 * kb + 1);
                }
                ML_LOAD_W3(ring + 8 * SLOT, bar_full + 8 * 8, 8);
                ML_LOAD_Y(ring + 9 * SLOT, bar_full + 8 * 9, 4);
            }
            __syncwarp();
            uint32_t slot = 0, phase = 1;
            for (int it = 10; it < 32; it++) {
                mbar_wait(bar_empty + 8 * slot, phase ^ 1);
                const uint32_t dst = ring + slot * SLOT, fb = bar_full + 8 * slot;
                if (el) {
                    if (it < 17) {
                        const int kb = 4 + (it - 8) / 3, r = (it - 8) % 3;
                        if (r == 1) ML_LOAD_Y(dst, fb, kb)
                        else ML_LOAD_W3(dst, fb, kb * 2 + (r >> 1))
                    } else if (it < 25) {
                        const int q = it - 17;
                        mbar_expect_tx(fb, 16384);
                        tma_load_3d_mc(dst + rank * 8192, &maps.w4a, fb, 0, fs * 224 + (q & 3) * 64, (q >> 2) * 2 + rank);
                    } else {
                        mbar_expect_tx(fb, 12288);
                        tma_load_3d_mc(dst + rank * 8192, &maps.w4b, fb, 0, fs * 224 + (it - 25) * 32 + rank * 16, 4);
                    }
                }
                if (++slot == ML_NSLOT) { slot = 0; phase ^= 1; }
            }
        }
    } else {
        reg_inc<ML_CREG>();
        const int wg = __shfl_sync(0xffffffffu, warp >> 2, 0);
        const int wq_ = warp & 3;
        const int tw = threadIdx.x & 127;
        const bool sig = tw == 0;
        const bool rsig = (wq_ < 2) && (lane == 0);
        const uint32_t rel_base = map_cluster(bar_empty, wq_ & 1);
        const int bar_me = 2 + wg, bar_other = 2 + (wg ^ 1), bar_wg = 4 + wg;
        if (wg == 1) named_arrive(2, 256);
        float* cs_s = (float*)(smem + ML_CS + wg * 896);
        const uint32_t ring16 = (ring & 0x3FFFF) >> 4;
        const uint64_t descK = make_desc(0, 16, 1024);
        const uint64_t descW = make_desc(0, 4096, 1024);
        const uint64_t descH = make_desc(0, 2048, 1024);
        float acc[112];
        uint32_t slot = 0, phase = 0, rel = 0;
#define ML_ADV() if (++slot == ML_NSLOT) { slot = 0; phase ^= 1; }
#define ML_REL() { if (rsig) mbar_arrive_cluster(rel_base + 8 * rel); if (++rel == ML_NSLOT) rel = 0; }
#define ML_REL3() { ML_REL(); ML_REL(); ML_REL(); }
#define ML_DRAIN(CNT)                                                  \
        if ((CNT) >= 3) { wg_wait<2>(); ML_REL(); }                    \
        if ((CNT) >= 2) { wg_wait<1>(); ML_REL(); }                    \
        wg_wait<0>(); ML_REL();

        const int r0 = tile * 128 + wg * 64 + wq_ * 16 + (lane >> 2);
        float2 sa[8], sb[8];
        float cs0 = 0.f, cs1 = 0.f;
        float4 gbv = make_float4(0.f, 0.f, 0.f, 0.f);
        const uint32_t* gbs = (const uint32_t*)(smem + ML_GB);
#pragma unroll
        for (int q = 0; q < 8; q++) { sa[q] = make_float2(0.f, 0.f); sb[q] = make_float2(0.f, 0.f); }
        float mean0 = 0.f, rstd0 = 0.f, mean1 = 0.f, rstd1 = 0.f;

        const uint32_t stg16 = (stg & 0x3FFFF) >> 4;
#pragma unroll 1
        for (int kb = 0; kb < 7; kb++) {
            const bool parked = kb < 4;
            const uint32_t sB1 = slot; mbar_wait(bar_full + 8 * slot, phase); ML_ADV();
            uint32_t a16;
            if (parked) { mbar_wait(bar_a + 8 * kb, 0); a16 = stg16 + kb * 1024; }
            else { a16 = ring16 + slot * 1024; mbar_wait(bar_full + 8 * slot, phase); ML_ADV(); }
            const uint32_t sB2 = slot; mbar_wait(bar_full + 8 * slot, phase); ML_ADV();
            if (kb <= 7 - ML_LAST) named_sync(bar_me, 256);
            const uint64_t da = descK + (a16 + wg * 512);
            const uint64_t db1 = descW + (ring16 + sB1 * 1024);
            const uint64_t db2 = descW + (ring16 + sB2 * 1024);
            wg_fence();
            wgmma_n224_ss(acc, da + 0, db1, kb > 0);
            wgmma_n224_ss(acc, da + 2, db1 + 128, 1);
            wg_commit();
            wgmma_n224_ss(acc, da + 4, db2, 1);
            wgmma_n224_ss(acc, da + 6, db2 + 128, 1);
            wg_commit();
            if (kb < 7 - ML_LAST || kb == 6) named_arrive(bar_other, 256);
            if (kb == 1) {
#pragma unroll
                for (int q = 0; q < 8; q++) {
                    asm volatile("ld.global.cg.v2.f32 {%0, %1}, [%2];" : "=f"(sa[q].x), "=f"(sa[q].y) : "l"(g_ystat + q * S_ + r0));
                    asm volatile("ld.global.cg.v2.f32 {%0, %1}, [%2];" : "=f"(sb[q].x), "=f"(sb[q].y) : "l"(g_ystat + q * S_ + r0 + 8));
                }
                asm volatile("ld.global.cg.f32 %0, [%1];" : "=f"(cs0) : "l"(g_colsum3 + fs * 224 + tw));
                if (tw < 96) asm volatile("ld.global.cg.f32 %0, [%1];" : "=f"(cs1) : "l"(g_colsum3 + fs * 224 + 128 + tw));
                if (wg == 0 && tw < 112)
                    asm volatile("ld.global.cg.v4.f32 {%0, %1, %2, %3}, [%4];" : "=f"(gbv.x), "=f"(gbv.y), "=f"(gbv.z), "=f"(gbv.w) : "l"(g_mod + 5 * D_ + tw * 4));
            }
            if (kb == 3) {
                float m = 0.f, n = 0.f;
#pragma unroll
                for (int q = 0; q < 8; q++) { m += sa[q].x; n += sb[q].x; }
                m *= 0.125f; n *= 0.125f;
                float v = 0.f, w = 0.f;
#pragma unroll
                for (int q = 0; q < 8; q++) {
                    v += fmaf(56.f * (sa[q].x - m), sa[q].x - m, sa[q].y);
                    w += fmaf(56.f * (sb[q].x - n), sb[q].x - n, sb[q].y);
                }
                mean0 = m; rstd0 = rsqrtf(v * (1.0f / D_) + LN_EPS);
                mean1 = n; rstd1 = rsqrtf(w * (1.0f / D_) + LN_EPS);
                cs_s[tw] = cs0;
                if (tw < 96) cs_s[128 + tw] = cs1;
                if (wg == 0 && tw < 112) *(uint2*)(smem + ML_GB + tw * 8) = make_uint2(pack_bf16(gbv.x, gbv.y), pack_bf16(gbv.z, gbv.w));
            }
            if (kb < 7 - ML_LAST) { wg_wait<1>(); ML_REL(); wg_wait<0>(); ML_REL(); if (!parked) ML_REL(); }
            if (kb == 6) {
                if (ML_LAST == 3) { wg_wait<5>(); ML_REL(); wg_wait<4>(); ML_REL(); ML_REL(); }
                if (ML_LAST >= 2) { wg_wait<3>(); ML_REL(); wg_wait<2>(); ML_REL(); ML_REL(); }
                wg_wait<1>(); ML_REL();
            }
        }
        wg_wait<0>();
        fence_regs(acc);
        ML_REL(); ML_REL();
        named_sync(bar_wg, 128);
        const int prow = tile * 128 + wg * 64;
        const uint64_t descQ = make_desc(0, 8192, 1024);
        uint32_t u[56];
        {
            const float k0 = 0.7978845608028654f, k1 = 0.7978845608028654f * 0.044715f;
            const float a0 = k0 * rstd0, b0 = k1 * rstd0 * rstd0 * rstd0, h0 = 0.5f * rstd0;
            const float a1 = k0 * rstd1, b1 = k1 * rstd1 * rstd1 * rstd1, h1 = 0.5f * rstd1;
#define ML_GELU(J0, J1)                                                                                  \
            _Pragma("unroll") for (int j = (J0); j < (J1); j++) {                                        \
                const float2 c2 = *(const float2*)(cs_s + j * 8 + (lane & 3) * 2);                       \
                float g[4];                                                                              \
                _Pragma("unroll") for (int q = 0; q < 4; q++) {                                          \
                    const float t = fmaf(-(q < 2 ? mean0 : mean1), (q & 1) ? c2.y : c2.x, acc[4 * j + q]);   \
                    const float w = fmaf(q < 2 ? b0 : b1, t * t, q < 2 ? a0 : a1);                       \
                    float th;                                                                            \
                    asm("tanh.approx.f32 %0, %1;" : "=f"(th) : "f"(t * w));                              \
                    const float hz = t * (q < 2 ? h0 : h1);                                              \
                    g[q] = fmaf(hz, th, hz);                                                             \
                }                                                                                        \
                u[2 * j] = pack_bf16(g[0], g[1]);                                                        \
                u[2 * j + 1] = pack_bf16(g[2], g[3]);                                                    \
            }
#define ML_PASS_A_PAIR(K0)                                                                               \
            {                                                                                            \
                if (((K0) & 3) == 0) { mbar_wait(bar_full + 8 * slot, phase); dbA = descQ + (ring16 + slot * 1024); ML_ADV(); } \
                wg_fence();                                                                              \
                wgmma_n128_rs(acc, u[4 * (K0)], u[4 * (K0) + 1], u[4 * (K0) + 2], u[4 * (K0) + 3], dbA + ((K0) & 3) * 128, (K0) != 0);       \
                wgmma_n128_rs(acc, u[4 * (K0) + 4], u[4 * (K0) + 5], u[4 * (K0) + 6], u[4 * (K0) + 7], dbA + ((K0) & 3) * 128 + 128, 1);     \
                if (((K0) & 3) == 2 || (K0) == 12) wg_commit();                                          \
            }
            uint64_t dbA = 0;
            ML_GELU(0, 16);
            ML_PASS_A_PAIR(0);  ML_GELU(16, 18);
            ML_PASS_A_PAIR(2);  ML_GELU(18, 20);
            ML_PASS_A_PAIR(4);  ML_GELU(20, 22);
            ML_PASS_A_PAIR(6);  ML_GELU(22, 24);
            wg_wait<1>(); ML_REL();
            ML_PASS_A_PAIR(8);  ML_GELU(24, 26);
            ML_PASS_A_PAIR(10); ML_GELU(26, 28);
            wg_wait<1>(); ML_REL();
            ML_PASS_A_PAIR(12);
            wg_wait<1>(); ML_REL();
            wg_wait<0>();
            fence_regs(acc);
            ML_REL();
        }
#define ML_OUT(NCOL, ACC, BUF, COL0)                                                                     \
        stage_tile_colscale<NCOL>(ACC, BUF, wg, wq_, lane, gbs + (COL0) / 2);                            \
        fence_proxy_async();                                                                             \
        named_sync(bar_wg, 128);                                                                         \
        if (sig) {                                                                                       \
            _Pragma("unroll") for (int b = 0; b < (NCOL) / 64; b++)                                      \
                tma_reduce_add_2d(&maps.part, (BUF) + b * 16384 + wg * 8192, (COL0) + b * 64, prow);     \
            bulk_commit();                                                                               \
        }
        ML_OUT(128, acc, stg, 0);
        {
            mbar_wait(bar_full + 8 * slot, phase);
            named_sync(bar_me, 256);
#pragma unroll
            for (int sq = 0; sq < 4; sq++) {
                if (sq > 0) mbar_wait(bar_full + 8 * slot, phase);
                const uint64_t db = descQ + (ring16 + slot * 1024);
                ML_ADV();
                wg_fence();
#pragma unroll
                for (int t = 0; t < (sq < 3 ? 4 : 2); t++)
                    wgmma_n128_rs(acc, u[16 * sq + 4 * t], u[16 * sq + 4 * t + 1], u[16 * sq + 4 * t + 2], u[16 * sq + 4 * t + 3], db + t * 128, (sq | t) != 0);
                wg_commit();
            }
            named_arrive(bar_other, 256);
            wg_wait<3>(); ML_REL();
            ML_DRAIN(3);
            fence_regs(acc);
        }
        ML_OUT(128, acc, stg + 2 * 16384, 128);
#define ML_G2_SLOT(KB, WAIT)                                                                             \
        {                                                                                                \
            if (WAIT) mbar_wait(bar_full + 8 * slot, phase);                                             \
            const uint64_t db = descH + (ring16 + slot * 1024);                                          \
            ML_ADV();                                                                                    \
            wg_fence();                                                                                  \
            wgmma_n192_rs(acc, u[8 * (KB) + 0], u[8 * (KB) + 1], u[8 * (KB) + 2], u[8 * (KB) + 3], db, (KB) > 0);    \
            wgmma_n192_rs(acc, u[8 * (KB) + 4], u[8 * (KB) + 5], u[8 * (KB) + 6], u[8 * (KB) + 7], db + 512, 1);     \
            wg_commit();                                                                                 \
        }
#define ML_TURN() mbar_wait(bar_full + 8 * slot, phase); named_sync(bar_me, 256);
        if (wg == 0) {
            ML_TURN(); ML_G2_SLOT(0, false); ML_G2_SLOT(1, true); ML_G2_SLOT(2, true);
            named_arrive(bar_other, 256); ML_DRAIN(3);
            ML_TURN(); ML_G2_SLOT(3, false); ML_G2_SLOT(4, true);
            named_arrive(bar_other, 256); ML_DRAIN(2);
            ML_TURN(); ML_G2_SLOT(5, false); ML_G2_SLOT(6, true);
            named_arrive(bar_other, 256); ML_DRAIN(2);
        } else {
            ML_TURN(); ML_G2_SLOT(0, false); ML_G2_SLOT(1, true);
            named_arrive(bar_other, 256); ML_DRAIN(2);
            ML_TURN(); ML_G2_SLOT(2, false); ML_G2_SLOT(3, true);
            named_arrive(bar_other, 256); ML_DRAIN(2);
            ML_TURN(); ML_G2_SLOT(4, false); ML_G2_SLOT(5, true); ML_G2_SLOT(6, true);
            ML_DRAIN(3);
        }
        fence_regs(acc);
        ML_OUT(192, acc, ring + 2 * SLOT, 256);
        if (sig) {
            bulk_wait_read0();
        }
    }
    __syncwarp();
    cluster_sync();
}

typedef CUresult (*EncodeTiledFn)(CUtensorMap*, CUtensorMapDataType, cuuint32_t, void*, const cuuint64_t*, const cuuint64_t*,
                                  const cuuint32_t*, const cuuint32_t*, CUtensorMapInterleave, CUtensorMapSwizzle,
                                  CUtensorMapL2promotion, CUtensorMapFloatOOBfill);
static EncodeTiledFn g_encode = nullptr;

static void make_map(CUtensorMap* m, const void* ptr, int rank, const uint64_t* dims, const uint64_t* strides_bytes,
                     const uint32_t* box, CUtensorMapSwizzle swz) {
    cuuint64_t gd[5], gs[5];
    cuuint32_t bx[5], es[5];
    for (int i = 0; i < rank; i++) { gd[i] = dims[i]; bx[i] = box[i]; es[i] = 1; }
    for (int i = 0; i + 1 < rank; i++) gs[i] = strides_bytes[i];
    CUresult r_ = g_encode(m, CU_TENSOR_MAP_DATA_TYPE_BFLOAT16, rank, const_cast<void*>(ptr), gd, gs, bx, es, CU_TENSOR_MAP_INTERLEAVE_NONE, swz,
             CU_TENSOR_MAP_L2_PROMOTION_L2_256B, CU_TENSOR_MAP_FLOAT_OOB_FILL_NONE);
    (void)r_;
}
static void map2d(CUtensorMap* m, const void* p, uint64_t cols, uint64_t rows, uint32_t bc, uint32_t br,
                  CUtensorMapSwizzle swz = CU_TENSOR_MAP_SWIZZLE_128B) {
    uint64_t d[2] = {cols, rows}, s[1] = {cols * 2};
    uint32_t b[2] = {bc, br};
    make_map(m, p, 2, d, s, b, swz);
}
static void map3d(CUtensorMap* m, const void* p, uint64_t cols, uint64_t rows, uint32_t br, uint32_t nb) {
    uint64_t d[3] = {64, rows, cols / 64}, s[2] = {cols * 2, 128};
    uint32_t b[3] = {64, br, nb};
    make_map(m, p, 3, d, s, b, CU_TENSOR_MAP_SWIZZLE_128B);
}

template <typename... KArgs, typename... Args>
static void launch_pdl(void (*kern)(KArgs...), int grid, int block, int smem, bool pdl, Args... args) {
    cudaLaunchConfig_t cfg = {};
    cfg.gridDim = dim3(grid);
    cfg.blockDim = dim3(block);
    cfg.dynamicSmemBytes = smem;
    cfg.stream = cudaStreamPerThread;
    cudaLaunchAttribute at[1];
    at[0].id = cudaLaunchAttributeProgrammaticStreamSerialization;
    at[0].val.programmaticStreamSerializationAllowed = 1;
    cfg.attrs = at;
    cfg.numAttrs = pdl ? 1 : 0;
    cudaLaunchKernelEx(&cfg, kern, args...);
}

struct HostState {
    bool init;
    const void* key[13];
    AttnMaps am;
    SmallMaps s1, s2;
    MlpMaps mm;
};
static HostState g_hs;

template <typename T> static void* sym_addr(T& sym) {
    void* p = nullptr;
    cudaGetSymbolAddress(&p, sym);
    return p;
}

extern "C" void kernel_launch(void* const* d_in, const int* in_sizes, int n_in, void* d_out, int out_size) {
    (void)in_sizes; (void)n_in; (void)out_size;
    const bf16* x = (const bf16*)d_in[0];
    const bf16* kc = (const bf16*)d_in[1];
    const bf16* vc = (const bf16*)d_in[2];
    const bf16* wq = (const bf16*)d_in[3];
    const bf16* wo = (const bf16*)d_in[4];
    const bf16* w1 = (const bf16*)d_in[6];
    const bf16* w2 = (const bf16*)d_in[7];
    const bf16* w3 = (const bf16*)d_in[8];
    const bf16* w4 = (const bf16*)d_in[9];
    const bf16* cvec = (const bf16*)d_in[10];
    const bf16* w_mod = (const bf16*)d_in[11];
    bf16* out = (bf16*)d_out;

    bool same = g_hs.init;
    for (int i = 0; i < 12 && same; i++) same = (g_hs.key[i] == d_in[i]);
    same = same && g_hs.key[12] == d_out;
    if (!same) {
        if (!g_encode) {
            void* fn = nullptr;
            cudaDriverEntryPointQueryResult qr;
            cudaGetDriverEntryPoint("cuTensorMapEncodeTiled", &fn, cudaEnableDefault, &qr);
            g_encode = (EncodeTiledFn)fn;
        }
        for (int i = 0; i < 12; i++) g_hs.key[i] = d_in[i];
        g_hs.key[12] = d_out;
        AttnMaps& am = g_hs.am;
        map2d(&am.h, sym_addr(g_H), D_, S_, 64, 128);
        map3d(&am.wq, wq, HQ * DH, D_, 16, 4);
        map2d(&am.k, kc, DH, HKV * SK, 64, 64);
        map3d(&am.v, vc, DH, HKV * SK, 16, 4);
        map3d(&am.wo4, wo, D_, HQ * DH, 16, 4);
        map3d(&am.wo3, wo, D_, HQ * DH, 16, 3);
        map2d(&am.park, sym_addr(g_park), DH, 128 * 128, 64, 64);
        map2d(&am.part, sym_addr(g_A), D_, S_, 64, 64);
        am.x = x; am.w1 = w1; am.w2 = w2; am.w3 = w3; am.w4 = w4; am.wo = wo;
        map2d(&g_hs.s1.a, sym_addr(g_hb), D_, S_, 64, 64);
        map2d(&g_hs.s1.w, w1, D_, D_, 64, 64);
        map2d(&g_hs.s1.out, sym_addr(g_G), D_, S_ + 4, 56, 64, CU_TENSOR_MAP_SWIZZLE_NONE);
        map2d(&g_hs.s1.res, sym_addr(g_hb), D_, S_, 56, 64, CU_TENSOR_MAP_SWIZZLE_NONE);
        map2d(&g_hs.s2.a, (bf16*)sym_addr(g_G) + 2 * D_, D_, S_, 64, 64);
        map2d(&g_hs.s2.w, w2, D_, D_, 64, 64);
        map2d(&g_hs.s2.out, sym_addr(g_y), D_, S_, 56, 64, CU_TENSOR_MAP_SWIZZLE_NONE);
        map2d(&g_hs.s2.res, sym_addr(g_hb), D_, S_, 56, 64, CU_TENSOR_MAP_SWIZZLE_NONE);
        map2d(&g_hs.s2.fin, out, D_, S_, 56, 64, CU_TENSOR_MAP_SWIZZLE_NONE);
        map2d(&g_hs.mm.y, sym_addr(g_y), D_, S_, 64, 128);
        map2d(&g_hs.mm.w3, w3, F_, D_, 64, 32);
        map3d(&g_hs.mm.w4a, w4, D_, F_, 64, 1);
        map3d(&g_hs.mm.w4b, w4, D_, F_, 16, 3);
        map2d(&g_hs.mm.part, out, D_, S_, 64, 64);
        cudaFuncSetAttribute(k_mod, cudaFuncAttributePreferredSharedMemoryCarveout, cudaSharedmemCarveoutMaxShared);
        cudaFuncSetAttribute(k_ln, cudaFuncAttributePreferredSharedMemoryCarveout, cudaSharedmemCarveoutMaxShared);
        cudaFuncSetAttribute(k_attn, cudaFuncAttributePreferredSharedMemoryCarveout, cudaSharedmemCarveoutMaxShared);
        cudaFuncSetAttribute(k_t0, cudaFuncAttributePreferredSharedMemoryCarveout, cudaSharedmemCarveoutMaxShared);
        cudaFuncSetAttribute(k_small<0>, cudaFuncAttributePreferredSharedMemoryCarveout, cudaSharedmemCarveoutMaxShared);
        cudaFuncSetAttribute(k_small<1>, cudaFuncAttributePreferredSharedMemoryCarveout, cudaSharedmemCarveoutMaxShared);
        cudaFuncSetAttribute(k_mlp, cudaFuncAttributePreferredSharedMemoryCarveout, cudaSharedmemCarveoutMaxShared);
        cudaFuncSetAttribute(k_attn, cudaFuncAttributeMaxDynamicSharedMemorySize, AT_SMEM);
        cudaFuncSetAttribute(k_small<0>, cudaFuncAttributeMaxDynamicSharedMemorySize, SG_SMEM);
        cudaFuncSetAttribute(k_small<1>, cudaFuncAttributeMaxDynamicSharedMemorySize, SG_SMEM);
        cudaFuncSetAttribute(k_mlp, cudaFuncAttributeMaxDynamicSharedMemorySize, ML_SMEM);
        g_hs.init = true;
    }
    launch_pdl(k_mod, MOD_BLOCKS, 256, 0, false, cvec, w_mod);
    launch_pdl(k_ln, 128, 512, 0, true, x, wq);
    launch_pdl(k_attn, 128, 384, AT_SMEM, true, g_hs.am);
    launch_pdl(k_t0, 128, 512, 0, true, x, out);
    launch_pdl(k_small<0>, 128, 256, SG_SMEM, true, g_hs.s1);
    launch_pdl(k_small<1>, 128, 256, SG_SMEM, true, g_hs.s2);
    launch_pdl(k_mlp, 128, 384, ML_SMEM, true, g_hs.mm);
}
```
